```python
import torch

def _softmax(x, axis=-1):
    return torch.softmax(x, dim=axis)

def _gelu(x):
    return torch.nn.functional.gelu(x, approximate='tanh')

def _silu(x):
    return torch.nn.functional.silu(x)

def _sigmoid(x):
    return torch.sigmoid(x)

def _layernorm(x, axis=-1, eps=1e-05):
    m = x.mean(dim=axis, keepdim=True)
    v = x.var(dim=axis, keepdim=True, unbiased=False)
    return (x - m) / torch.sqrt(v + eps)

def _scatter_add(tgt, idx, src, axis=0):
    return tgt.clone().index_add_(axis, idx, src)

def _segment_sum(src, seg, n):
    out = torch.zeros((n,) + src.shape[1:], dtype=src.dtype)
    return out.index_add_(0, seg, src)

def _pad(x, pw):
    flat = tuple((v for pair in reversed(pw) for v in pair))
    return torch.nn.functional.pad(x, flat)
kernel_name = 'standalone__autoregressive_conv_wavenet__speech'

def setup_inputs():

    _w = lambda a: (lambda t: t.to(torch.bfloat16) if t.is_floating_point() else t)(torch.as_tensor(a))
    B, T, D, K = (2, 1000, 512, 5)
    return {'x': _w((lambda *s: torch.randn(*s, dtype=torch.bfloat16) * 0.1)(B, T, D)), 'w': _w((lambda *s: torch.randn(*s, dtype=torch.bfloat16) * 0.1)(K, D, 2 * D)), 'w_o': _w((lambda *s: torch.randn(*s, dtype=torch.bfloat16) * 0.05)(D, D))}

def reference(x, w, w_o):
    B, T, D = x.shape
    K = w.shape[0]
    dil = 2
    pad = (K - 1) * dil
    xp = _pad(x, ((0, 0), (pad, 0), (0, 0)))
    h = torch.einsum('btc,cd->btd', xp[:, pad:pad + T, :], w[0])
    for i in range(1, K):
        off = pad - i * dil
        h = h + torch.einsum('btc,cd->btd', xp[:, off:off + T, :], w[i])
    f = h[..., :D].clone()
    g = h[..., D:].clone()
    z = torch.tanh(f) * _sigmoid(g)
    return z @ w_o
```

```cpp
#include <cuda_runtime.h>
#include <cuda_bf16.h>
#include <cuda.h>
#include <stdint.h>

namespace {

constexpr int T_LEN   = 1000;
constexpr int D_CH    = 512;
constexpr int NTOK    = 256;
constexpr int XROWS   = NTOK + 8;
constexpr int XBYTES  = XROWS * 128;
constexpr int XBOX    = 88;
constexpr int XST     = 2;
constexpr int WST     = 4;
constexpr int WBYTES  = 8192;
constexpr int WO_BYTES = 131072;

constexpr int SM_WO   = 0;
constexpr int SM_X    = SM_WO + WO_BYTES;
constexpr int SM_W    = SM_X + XST * XBYTES;
constexpr int SM_BAR  = SM_W + WST * WBYTES;
constexpr int SM_TOTAL = SM_BAR + 256;
__host__ __device__ constexpr int sm_zin(int i) { return SM_X + (i >> 1) * XBYTES + (i & 1) * 16384; }
constexpr int SM_OSTG  = SM_W;

constexpr int BAR_WFULL  = 0;
constexpr int BAR_WEMPTY = BAR_WFULL + WST;
constexpr int BAR_XFULL  = BAR_WEMPTY + WST;
constexpr int BAR_XEMPTY = BAR_XFULL + XST;
constexpr int BAR_WO     = BAR_XEMPTY + XST;
constexpr int BAR_PAR    = BAR_WO + 1;
constexpr int BAR_Z      = BAR_PAR + 1;
constexpr int BAR_RETRY  = BAR_Z + 4;

constexpr int SM_CONST = SM_BAR + 232;
constexpr int SM_PAR   = SM_BAR + 240;
constexpr int NTHREADS = 192;
#define SCHED 0
#define ORDER 1
#define EARLY 0
#define ZDELAY 700

__device__ uint4 g_zx[2][8 * 4 * 4096];
__device__ unsigned int g_ticket;

#define PROF(i)
#define PROFG(i)

__device__ __forceinline__ uint32_t smem_u32(const void* p) { return (uint32_t)__cvta_generic_to_shared(p); }

__device__ __forceinline__ void mbar_init(uint32_t bar, uint32_t cnt) {
    asm volatile("mbarrier.init.shared::cta.b64 [%0], %1;" ::"r"(bar), "r"(cnt));
}
__device__ __forceinline__ void mbar_expect_tx(uint32_t bar, uint32_t bytes) {
    asm volatile("mbarrier.arrive.expect_tx.shared::cta.b64 _, [%0], %1;" ::"r"(bar), "r"(bytes) : "memory");
}
__device__ __forceinline__ void mbar_arrive(uint32_t bar) {
    asm volatile("mbarrier.arrive.shared::cta.b64 _, [%0];" ::"r"(bar) : "memory");
}
__device__ __forceinline__ void mbar_wait(uint32_t bar, uint32_t parity) {
    asm volatile(
        "{\n"
        ".reg .pred p;\n"
        "WAIT_LOOP:\n"
        "mbarrier.try_wait.parity.shared::cta.b64 p, [%0], %1;\n"
        "@p bra WAIT_DONE;\n"
        "bra WAIT_LOOP;\n"
        "WAIT_DONE:\n"
        "}\n" ::"r"(bar), "r"(parity) : "memory");
}
__device__ __forceinline__ void tma_load_3d(uint32_t dst, const CUtensorMap* m, uint32_t bar, int c0, int c1, int c2) {
    asm volatile("cp.async.bulk.tensor.3d.shared::cluster.global.mbarrier::complete_tx::bytes [%0], [%1, {%3, %4, %5}], [%2];"
                 ::"r"(dst), "l"(m), "r"(bar), "r"(c0), "r"(c1), "r"(c2) : "memory");
}
__device__ __forceinline__ void tma_load_2d(uint32_t dst, const CUtensorMap* m, uint32_t bar, int c0, int c1) {
    asm volatile("cp.async.bulk.tensor.2d.shared::cluster.global.mbarrier::complete_tx::bytes [%0], [%1, {%3, %4}], [%2];"
                 ::"r"(dst), "l"(m), "r"(bar), "r"(c0), "r"(c1) : "memory");
}
__device__ __forceinline__ void prefetch_l2(const void* p) { asm volatile("prefetch.global.L2 [%0];" ::"l"(p)); }
__device__ __forceinline__ void fence_proxy_async_smem() { asm volatile("fence.proxy.async.shared::cta;" ::: "memory"); }
__device__ __forceinline__ void prefetch_tmap(const CUtensorMap* m) {
    asm volatile("prefetch.tensormap [%0];" ::"l"(m) : "memory");
}
__device__ __forceinline__ void wgmma_fence() { asm volatile("wgmma.fence.sync.aligned;" ::: "memory"); }
__device__ __forceinline__ void wgmma_commit() { asm volatile("wgmma.commit_group.sync.aligned;" ::: "memory"); }
template <int N> __device__ __forceinline__ void wgmma_wait() {
    asm volatile("wgmma.wait_group.sync.aligned %0;" ::"n"(N) : "memory");
}
template <int N> __device__ __forceinline__ void fence_regs(float (&d)[N]) {
#pragma unroll
    for (int i = 0; i < N; i++) asm volatile("" : "+f"(d[i]) :: "memory");
}
__device__ __forceinline__ void ldsm_x4_trans(uint32_t (&r)[4], uint32_t addr) {
    asm volatile("ldmatrix.sync.aligned.m8n8.x4.trans.shared.b16 {%0, %1, %2, %3}, [%4];"
                 : "=r"(r[0]), "=r"(r[1]), "=r"(r[2]), "=r"(r[3]) : "r"(addr) : "memory");
}
__device__ __forceinline__ void stsm_x4(uint32_t addr, uint32_t a, uint32_t b, uint32_t c, uint32_t d) {
    asm volatile("stmatrix.sync.aligned.m8n8.x4.shared.b16 [%0], {%1, %2, %3, %4};"
                 ::"r"(addr), "r"(a), "r"(b), "r"(c), "r"(d) : "memory");
}
__device__ __forceinline__ void st_relaxed_v4(void* p, uint32_t a, uint32_t b, uint32_t c, uint32_t d) {
    asm volatile("st.relaxed.gpu.global.v4.b32 [%0], {%1, %2, %3, %4};" ::"l"(p), "r"(a), "r"(b), "r"(c), "r"(d) : "memory");
}
__device__ __forceinline__ void bulk_load(uint32_t dst, const void* src, uint32_t bytes, uint32_t bar) {
    asm volatile("cp.async.bulk.shared::cluster.global.mbarrier::complete_tx::bytes [%0], [%1], %2, [%3];"
                 ::"r"(dst), "l"(src), "r"(bytes), "r"(bar) : "memory");
}
__device__ __forceinline__ uint32_t clock_now() {
    uint32_t t;
    asm volatile("mov.u32 %0, %%clock;" : "=r"(t) :: "memory");
    return t;
}
__device__ __forceinline__ float tanh_fast(float x) {
    float y;
    asm("tanh.approx.f32 %0, %1;" : "=f"(y) : "f"(x));
    return y;
}
__device__ __forceinline__ uint32_t pack_bf16(float lo, float hi) {
    uint32_t r;
    asm("cvt.rn.bf16x2.f32 %0, %1, %2;" : "=r"(r) : "f"(hi), "f"(lo));
    return r;
}
__device__ __forceinline__ uint64_t make_desc(uint32_t addr, uint32_t lbo_bytes, uint32_t sbo_bytes) {
    return (uint64_t)((addr & 0x3FFFF) >> 4) | ((uint64_t)(lbo_bytes >> 4) << 16) | ((uint64_t)(sbo_bytes >> 4) << 32) |
           ((uint64_t)1 << 62);
}

#define R8(d, o) "+f"(d[o + 0]), "+f"(d[o + 1]), "+f"(d[o + 2]), "+f"(d[o + 3]), "+f"(d[o + 4]), "+f"(d[o + 5]), "+f"(d[o + 6]), "+f"(d[o + 7])

__device__ __forceinline__ void wgmma_m64n128k16_rs(float (&d)[64], const uint32_t (&a)[4], uint64_t descB, int scale_d) {
    asm volatile(
        "{\n"
        ".reg .pred p;\n"
        "setp.ne.b32 p, %69, 0;\n"
        "wgmma.mma_async.sync.aligned.m64n128k16.f32.bf16.bf16 "
        "{%0, %1, %2, %3, %4, %5, %6, %7, %8, %9, %10, %11, %12, %13, %14, %15, "
        "%16, %17, %18, %19, %20, %21, %22, %23, %24, %25, %26, %27, %28, %29, %30, %31, "
        "%32, %33, %34, %35, %36, %37, %38, %39, %40, %41, %42, %43, %44, %45, %46, %47, "
        "%48, %49, %50, %51, %52, %53, %54, %55, %56, %57, %58, %59, %60, %61, %62, %63}, "
        "{%64, %65, %66, %67}, %68, p, -1, 1, 1;\n"
        "}\n"
        : R8(d, 0), R8(d, 8), R8(d, 16), R8(d, 24), R8(d, 32), R8(d, 40), R8(d, 48), R8(d, 56)
        : "r"(a[0]), "r"(a[1]), "r"(a[2]), "r"(a[3]), "l"(descB), "r"(scale_d));
}

template <int OFF>
__device__ __forceinline__ void wgmma_m64n128k16_rs_half(float (&d)[128], const uint32_t (&a)[4], uint64_t descB) {
    asm volatile(
        "wgmma.mma_async.sync.aligned.m64n128k16.f32.bf16.bf16 "
        "{%0, %1, %2, %3, %4, %5, %6, %7, %8, %9, %10, %11, %12, %13, %14, %15, "
        "%16, %17, %18, %19, %20, %21, %22, %23, %24, %25, %26, %27, %28, %29, %30, %31, "
        "%32, %33, %34, %35, %36, %37, %38, %39, %40, %41, %42, %43, %44, %45, %46, %47, "
        "%48, %49, %50, %51, %52, %53, %54, %55, %56, %57, %58, %59, %60, %61, %62, %63}, "
        "{%64, %65, %66, %67}, %68, 1, 1, 1, 0;\n"
        : R8(d, OFF + 0), R8(d, OFF + 8), R8(d, OFF + 16), R8(d, OFF + 24), R8(d, OFF + 32), R8(d, OFF + 40), R8(d, OFF + 48), R8(d, OFF + 56)
        : "r"(a[0]), "r"(a[1]), "r"(a[2]), "r"(a[3]), "l"(descB));
}
template <int OFF> __device__ __forceinline__ void fence_half(float (&d)[128]) {
#pragma unroll
    for (int i = 0; i < 64; i++) asm volatile("" : "+f"(d[OFF + i]) :: "memory");
}

template <int V> struct IC { static constexpr int value = V; };

template <int Q0, int N> struct GateGroup { static constexpr int J = 2 * (Q0 ^ (N >> 1)) + (N & 1); };

template <int Q0, int N, int LO = 0, int HI = 16>
__device__ __forceinline__ void gate_mufu(float (&acc)[128], float one, float half) {
    constexpr int J = GateGroup<Q0, N>::J;
#pragma unroll
    for (int i = LO; i < HI; i++) acc[16 * J + i] = tanh_fast(((i & 2) ? half : one) * acc[16 * J + i]);
}
__device__ __forceinline__ void pin_scales(uint32_t sc_addr, float& one, float& half) {
    asm volatile("bar.arrive 6, 128;" ::: "memory");
    asm volatile("ld.volatile.shared.v2.f32 {%0, %1}, [%2];" : "=f"(one), "=f"(half) : "r"(sc_addr) : "memory");
}
template <int Q0, int N>
__device__ __forceinline__ void gate_finish(float (&acc)[128], uint8_t* zdst, float half) {
    constexpr int J = GateGroup<Q0, N>::J;
    uint32_t zp[4];
    const float nh = -half;
#pragma unroll
    for (int i = 0; i < 4; i++) {
        const int r = 16 * J + 4 * i;
        zp[i] = __vmaxu2(pack_bf16(acc[r] * fmaf(acc[r + 2], nh, nh), acc[r + 1] * fmaf(acc[r + 3], nh, nh)), 0x00010001u);
    }
    st_relaxed_v4(zdst + (J >> 1) * 65536 + (J & 1) * 8192, zp[0], zp[1], zp[2], zp[3]);
    if (N & 1) asm volatile("bar.arrive %0, 160;" ::"n"(2 + (N >> 1)) : "memory");
}

template <int Q0>
__device__ __forceinline__ void tail_gemm1(float (&acc)[128], uint32_t (&afr)[2][4][4], uint32_t sb, int ws, int wph, uint32_t a_lane_off,
                                           uint8_t* zdst, int lane) {
    constexpr int OA = (Q0 >> 1) * 64;
    constexpr int OB = 64 - OA;
    const uint32_t bars = sb + SM_BAR;
    const uint32_t sc_addr = sb + SM_CONST;
    uint32_t keep[4][4], ext[4][4];
    const int ws0 = ws;
    auto wtile = [&](int tap) { return sb + SM_W + ((ws0 + tap) & (WST - 1)) * WBYTES + a_lane_off; };
    auto wwait = [&](int tap) {
        const int st = ws0 + tap;
        mbar_wait(bars + 8 * (BAR_WFULL + (st & (WST - 1))), wph ^ ((st >> 2) & 1));
    };
    auto load = [&](uint32_t (&f)[4][4], int tap) {
        const uint32_t wa = wtile(tap);
#pragma unroll
        for (int kk = 0; kk < 4; kk++) ldsm_x4_trans(f[kk], wa + kk * 1024);
    };
    auto issueA = [&](uint32_t (&f)[4][4], int tap) {
        const uint64_t db = make_desc(sb + SM_X + XBYTES + (8 - 2 * tap) * 128 + OA * 256, 16, 1024);
        wgmma_fence();
#pragma unroll
        for (int kk = 0; kk < 4; kk++) wgmma_m64n128k16_rs_half<OA>(acc, f[kk], db + kk * 2);
        wgmma_commit();
    };
    auto issueB = [&](uint32_t (&f)[4][4], int tap) {
        const uint64_t db = make_desc(sb + SM_X + XBYTES + (8 - 2 * tap) * 128 + OB * 256, 16, 1024);
        wgmma_fence();
#pragma unroll
        for (int kk = 0; kk < 4; kk++) wgmma_m64n128k16_rs_half<OB>(acc, f[kk], db + kk * 2);
        wgmma_commit();
    };
    mbar_wait(bars + 8 * (BAR_XFULL + 1), 1);
    wwait(0); load(keep, 0);
    __syncwarp();
    if (lane == 0) mbar_arrive(bars + 8 * (BAR_WEMPTY + ws0));
    wwait(1); load(afr[1], 1);
    wwait(2); load(ext, 2);
    issueA(keep, 0);   wgmma_wait<1>();
    wwait(3); load(afr[0], 3);
    issueA(afr[1], 1); wgmma_wait<1>();
    issueA(ext, 2);    wgmma_wait<1>();
    wwait(4); load(afr[1], 4);
    issueA(afr[0], 3); wgmma_wait<1>();
    issueA(afr[1], 4); wgmma_wait<1>();
    if (threadIdx.x == 0) PROF(24);
    float one, half;
    issueB(keep, 0);   wgmma_wait<1>();
    fence_half<OA>(acc);
    pin_scales(sc_addr, one, half);
    gate_mufu<Q0, 0>(acc, one, half);
    issueB(ext, 2);    wgmma_wait<1>();
    load(keep, 1);
    pin_scales(sc_addr, one, half);
    gate_finish<Q0, 0>(acc, zdst, half); gate_mufu<Q0, 1>(acc, one, half);
    issueB(afr[0], 3); wgmma_wait<1>();
    pin_scales(sc_addr, one, half);
    gate_finish<Q0, 1>(acc, zdst, half); gate_mufu<Q0, 2>(acc, one, half);
    issueB(afr[1], 4); wgmma_wait<1>();
    pin_scales(sc_addr, one, half);
    gate_finish<Q0, 2>(acc, zdst, half); gate_mufu<Q0, 3>(acc, one, half);
    issueB(keep, 1);   wgmma_wait<1>();
    pin_scales(sc_addr, one, half);
    gate_finish<Q0, 3>(acc, zdst, half);
    wgmma_wait<0>();
    fence_half<OB>(acc);
    if (threadIdx.x == 0) PROF(3);
    gate_mufu<Q0, 4>(acc, 1.0f, 0.5f);
    gate_mufu<Q0, 5>(acc, 1.0f, 0.5f);
    gate_finish<Q0, 4>(acc, zdst, 0.5f);
    pin_scales(sc_addr, one, half);
    gate_mufu<Q0, 6>(acc, one, half);
    gate_finish<Q0, 5>(acc, zdst, 0.5f);
    pin_scales(sc_addr, one, half);
    gate_mufu<Q0, 7>(acc, one, half);
    gate_finish<Q0, 6>(acc, zdst, 0.5f);
    gate_finish<Q0, 7>(acc, zdst, 0.5f);
}

__device__ __forceinline__ void fetch_slot(int i, uint32_t sb, const uint8_t* zsrc, int q, int lane) {
    const uint32_t bars = sb + SM_BAR;
    asm volatile("bar.sync %0, 160;" ::"r"(2 + i) : "memory");
    const uint32_t t = clock_now();
    if (lane == 0) {
        while (clock_now() - t < (uint32_t)ZDELAY) {}
        mbar_expect_tx(bars + 8 * (BAR_Z + i), 16384);
        bulk_load(sb + sm_zin(i), zsrc + (q ^ i) * 16384, 16384, bars + 8 * (BAR_Z + i));
        PROF(26 + i);
    }
    __syncwarp();
}

template <int I>
__device__ __forceinline__ void z_load(uint32_t (&z)[8][4], uint32_t sb, int warp, int lane) {
    mbar_wait(sb + SM_BAR + 8 * (BAR_Z + I), 0);
#pragma unroll
    for (int j = 0; j < 8; j++) ldsm_x4_trans(z[j], sb + sm_zin(I) + warp * 4096 + j * 512 + lane * 16);
}
__device__ __forceinline__ bool z_check(const uint32_t (&z)[8][4]) {
    uint32_t m0 = 0xFFFFFFFFu, m1 = 0xFFFFFFFFu;
#pragma unroll
    for (int j = 0; j < 8; j++) {
        m0 = __vimin3_u16x2(m0, z[j][0], z[j][1]);
        m1 = __vimin3_u16x2(m1, z[j][2], z[j][3]);
    }
    m0 = __vminu2(m0, m1);
    return __all_sync(0xffffffffu, ((m0 & 0xFFFFu) != 0u) && ((m0 >> 16) != 0u));
}
__device__ __forceinline__ void z_issue(float (&acc2)[64], uint32_t (&z)[8][4], uint32_t sb, int beta) {
#pragma unroll
    for (int j = 0; j < 8; j++) asm volatile("" : "+r"(z[j][0]), "+r"(z[j][1]), "+r"(z[j][2]), "+r"(z[j][3]) :: "memory");
    const uint64_t db = make_desc(sb + SM_WO + beta * 16384, 65536, 1024);
    wgmma_fence();
#pragma unroll
    for (int j = 0; j < 8; j++) wgmma_m64n128k16_rs(acc2, z[j], db + j * 128, 1);
    wgmma_commit();
}
__device__ __forceinline__ bool wg_any(bool p) {
    uint32_t r;
    asm volatile("{\n.reg .pred a, b;\nsetp.ne.u32 a, %1, 0;\nbarrier.cta.red.or.aligned.pred b, 1, 128, a;\nselp.u32 %0, 1, 0, b;\n}\n"
                 : "=r"(r) : "r"((uint32_t)p) : "memory");
    return r != 0;
}
template <int I>
__device__ __forceinline__ void z_repair(float (&acc2)[64], uint32_t (&z)[8][4], uint32_t sb, const uint8_t* src, int beta, int warp,
                                         int lane, uint32_t mine, uint32_t& rph) {
    if (!wg_any(mine != 0u)) return;
    if (mine) {
        const uint32_t zs = sb + sm_zin(I) + warp * 4096;
        const uint32_t bar = sb + SM_BAR + 8 * (BAR_RETRY + warp);
        uint32_t zn[8][4];
        int spins = 0;
        do {
            __syncwarp();
            if (lane == 0) {
                mbar_expect_tx(bar, 4096);
                bulk_load(zs, src, 4096, bar);
            }
            mbar_wait(bar, rph);
            rph ^= 1;
#pragma unroll
            for (int j = 0; j < 8; j++) ldsm_x4_trans(zn[j], zs + j * 512 + lane * 16);
        } while (!z_check(zn) && ++spins < (1 << 16));
#pragma unroll
        for (int j = 0; j < 8; j++)
#pragma unroll
            for (int k = 0; k < 4; k++) z[j][k] = zn[j][k] & __vcmpeq2(z[j][k], 0u);
    } else {
#pragma unroll
        for (int j = 0; j < 8; j++)
#pragma unroll
            for (int k = 0; k < 4; k++) z[j][k] = 0u;
    }
    z_issue(acc2, z, sb, beta);
    wgmma_wait<0>();
}

__global__ void __launch_bounds__(NTHREADS, 1)
wavenet_fused_kernel(const __grid_constant__ CUtensorMap mapX, const __grid_constant__ CUtensorMap mapW,
                     const __grid_constant__ CUtensorMap mapWo, const __nv_bfloat16* __restrict__ xg,
                     const __nv_bfloat16* __restrict__ wg, __nv_bfloat16* __restrict__ out) {
    extern __shared__ __align__(1024) uint8_t smem_raw[];
    const uint32_t sb = smem_u32(smem_raw);
    const uint32_t bars = sb + SM_BAR;
    const int warp = threadIdx.x >> 5;
    const int lane = threadIdx.x & 31;
    const int cg = blockIdx.x & 15;
    const int tt = blockIdx.x >> 4;
    const int batch = tt >> 2;
    const int t0 = (tt & 3) * NTOK;
    const int c4 = cg & 3, q = cg >> 2;

    if (threadIdx.x == 160) {
        prefetch_tmap(&mapW);
        prefetch_tmap(&mapX);
    }
    if (threadIdx.x == 128) {
        PROFG(0);
        for (int i = 0; i < WST; i++) { mbar_init(bars + 8 * (BAR_WFULL + i), 1); mbar_init(bars + 8 * (BAR_WEMPTY + i), 4); }
        for (int i = 0; i < XST; i++) { mbar_init(bars + 8 * (BAR_XFULL + i), 1); mbar_init(bars + 8 * (BAR_XEMPTY + i), 4); }
        mbar_init(bars + 8 * BAR_WO, 1);
        mbar_init(bars + 8 * BAR_PAR, 1);
        for (int i = 0; i < 4; i++) {
            mbar_init(bars + 8 * (BAR_Z + i), 1);
            mbar_init(bars + 8 * (BAR_RETRY + i), 1);
        }
        asm volatile("st.shared.v2.f32 [%0], {%1, %2};" ::"r"(sb + SM_CONST), "f"(1.0f), "f"(0.5f) : "memory");
        asm volatile("fence.mbarrier_init.release.cluster;" ::: "memory");
        fence_proxy_async_smem();
        const uint32_t xf = bars + 8 * BAR_XFULL;
        mbar_expect_tx(xf, XBYTES);
        mbar_expect_tx(bars + 8 * BAR_WFULL, WBYTES);
        tma_load_3d(sb + SM_W, &mapW, bars + 8 * BAR_WFULL, cg * 32, 0, 0);
#pragma unroll
        for (int j = 0; j < 3; j++) tma_load_3d(sb + SM_X + j * XBOX * 128, &mapX, xf, 0, t0 - 8 + j * XBOX, batch);
    }
    __syncthreads();

    if (warp >= 4) {
        if (warp == 4) {
            if (lane == 0) {
                int ws = 1, wph = 1;
                for (int kc = 0; kc < 8; kc++) {
                    const int xs = kc & 1;
                    if (kc > 0) {
                        mbar_wait(bars + 8 * (BAR_XEMPTY + xs), ((kc >> 1) & 1) ^ 1);
                        const uint32_t xf = bars + 8 * (BAR_XFULL + xs);
                        mbar_expect_tx(xf, XBYTES);
                        const uint32_t xd = sb + SM_X + xs * XBYTES;
#pragma unroll
                        for (int j = 0; j < 3; j++) tma_load_3d(xd + j * XBOX * 128, &mapX, xf, kc * 64, t0 - 8 + j * XBOX, batch);
                    } else {
                        prefetch_tmap(&mapWo);
                    }
                    for (int tap = (kc == 0 ? 1 : 0); tap < 5; tap++) {
                        mbar_wait(bars + 8 * (BAR_WEMPTY + ws), wph);
                        const uint32_t wf = bars + 8 * (BAR_WFULL + ws);
                        mbar_expect_tx(wf, WBYTES);
                        tma_load_3d(sb + SM_W + ws * WBYTES, &mapW, wf, cg * 32, tap * 512 + kc * 64, 0);
                        if (++ws == WST) { ws = 0; wph ^= 1; }
                        const int it = kc * 5 + tap - 10;
                        if (it >= 0 && it < 16) {
                            const uint32_t wob = bars + 8 * BAR_WO;
                            if (it == 0) mbar_expect_tx(wob, WO_BYTES);
                            tma_load_2d(sb + SM_WO + (it & 1) * 65536 + (it >> 1) * 8192, &mapWo, wob, c4 * 128 + (it & 1) * 64, (it >> 1) * 64);
                        }
                    }
                }
            }
            __syncwarp();
        } else {
            unsigned int par = 0;
            if (lane == 0) par = (atomicAdd(&g_ticket, 1u) >> 7) & 1u;
            par = __shfl_sync(0xffffffffu, par, 0);
            __nanosleep(1500);
            uint4* mine = &g_zx[par][tt * 4 * 4096 + q * 1024 + 2 * c4 * 32];
#pragma unroll 1
            for (int i = 0; i < 32; i++) {
                mine[(i >> 3) * 4096 + ((i >> 1) & 3) * 256 + (i & 1) * 32 + lane] = make_uint4(0u, 0u, 0u, 0u);
                __nanosleep(100);
            }
            __syncwarp();
            if (lane == 0) {
                asm volatile("st.shared.u32 [%0], %1;" ::"r"(sb + SM_PAR), "r"(par) : "memory");
                mbar_arrive(bars + 8 * BAR_PAR);
            }
            uint4* clr = &g_zx[par ^ 1][blockIdx.x * 1024];
#pragma unroll 1
            for (int i = 0; i < 32; i++) {
                clr[i * 32 + lane] = make_uint4(0u, 0u, 0u, 0u);
                __nanosleep(100);
            }
        }
        mbar_wait(bars + 8 * BAR_PAR, 0);
        uint32_t par;
        asm volatile("ld.shared.u32 %0, [%1];" : "=r"(par) : "r"(sb + SM_PAR) : "memory");
        const uint8_t* zsrc = reinterpret_cast<const uint8_t*>(&g_zx[par][(tt * 4 + q) * 4096]);
        fetch_slot(5 - warp, sb, zsrc, q, lane);
        fetch_slot(7 - warp, sb, zsrc, q, lane);
    } else {
        float acc[128];
#pragma unroll
        for (int i = 0; i < 128; i++) acc[i] = 0.f;
        uint32_t afr[2][4][4];
        const int lk = ((lane >> 4) << 3) + (lane & 7);
        const uint32_t a_lane_off = ((lane >> 3) & 1) * 4096 + lk * 64 + ((warp ^ ((lk >> 1) & 3)) << 4);
        int ws = 0, wph = 0;
        uint32_t par = 0;
        if (threadIdx.x == 0) PROF(1);
#pragma unroll 1
        for (int kc2 = 0; kc2 < 4; kc2++) {
#pragma unroll
            for (int u = 0; u < 10; u++) {
                const int xs = u / 5;
                const int tap = u % 5;
                if (u == 5 && kc2 == 3) break;
                if (tap == 0) mbar_wait(bars + 8 * (BAR_XFULL + xs), kc2 & 1);
                mbar_wait(bars + 8 * (BAR_WFULL + ws), wph);
                if (kc2 == 0 && u == 0 && threadIdx.x == 0) PROF(2);
                const uint32_t wa = sb + SM_W + ws * WBYTES + a_lane_off;
#pragma unroll
                for (int kk = 0; kk < 4; kk++) ldsm_x4_trans(afr[u & 1][kk], wa + kk * 1024);
                __syncwarp();
                if (lane == 0) mbar_arrive(bars + 8 * (BAR_WEMPTY + ws));
                if (++ws == WST) { ws = 0; wph ^= 1; }
                const uint64_t db = make_desc(sb + SM_X + xs * XBYTES + (8 - 2 * tap) * 128, 16, 1024);
                wgmma_fence();
#pragma unroll
                for (int kk = 0; kk < 4; kk++) {
                    wgmma_m64n128k16_rs_half<0>(acc, afr[u & 1][kk], db + kk * 2);
                    wgmma_m64n128k16_rs_half<64>(acc, afr[u & 1][kk], db + kk * 2 + 1024);
                }
                wgmma_commit();
                if (u == 2 && kc2 == 3) {
                    mbar_wait(bars + 8 * BAR_PAR, 0);
                    asm volatile("ld.shared.u32 %0, [%1];" : "=r"(par) : "r"(sb + SM_PAR) : "memory");
                    mbar_wait(bars + 8 * BAR_WO, 0);
                }
                wgmma_wait<1>();
                if (tap == 0 && (u > 0 || kc2 > 0)) {
                    if (lane == 0) mbar_arrive(bars + 8 * (BAR_XEMPTY + (xs ^ 1)));
                }
            }
        }
        uint8_t* zx = reinterpret_cast<uint8_t*>(&g_zx[par][tt * 4 * 4096]);
        uint8_t* zdst = zx + q * 16384 + (2 * c4 + (warp >> 1)) * 512 + (warp & 1) * 256 +
                        ((lane >> 1) & 1) * 4096 + (lane & 1) * 128 + (lane >> 2) * 16;
        switch (q) {
            case 0: tail_gemm1<0>(acc, afr, sb, ws, wph, a_lane_off, zdst, lane); break;
            case 1: tail_gemm1<1>(acc, afr, sb, ws, wph, a_lane_off, zdst, lane); break;
            case 2: tail_gemm1<2>(acc, afr, sb, ws, wph, a_lane_off, zdst, lane); break;
            default: tail_gemm1<3>(acc, afr, sb, ws, wph, a_lane_off, zdst, lane); break;
        }
        if (threadIdx.x == 0) PROF(4);

        float acc2[64];
#pragma unroll
        for (int i = 0; i < 64; i++) acc2[i] = 0.f;
        {
            uint32_t za[4][8][4];
            uint32_t bad;
            z_load<0>(za[0], sb, warp, lane);
            bad = z_check(za[0]) ? 0u : 1u;
            if (threadIdx.x == 0) PROF(12);
            z_issue(acc2, za[0], sb, q ^ 0);
            z_load<1>(za[1], sb, warp, lane);
            bad |= z_check(za[1]) ? 0u : 2u;
            if (threadIdx.x == 0) PROF(13);
            z_issue(acc2, za[1], sb, q ^ 1);
            z_load<2>(za[2], sb, warp, lane);
            bad |= z_check(za[2]) ? 0u : 4u;
            if (threadIdx.x == 0) PROF(14);
            z_issue(acc2, za[2], sb, q ^ 2);
            z_load<3>(za[3], sb, warp, lane);
            bad |= z_check(za[3]) ? 0u : 8u;
            if (threadIdx.x == 0) PROF(15);
            z_issue(acc2, za[3], sb, q ^ 3);
            const bool any_bad = wg_any(bad != 0u);
            wgmma_wait<0>();
            if (__builtin_expect(any_bad, 0)) {
                const uint8_t* zsrc = zx + q * 65536 + warp * 4096;
                uint32_t rph = 0;
                z_repair<0>(acc2, za[0], sb, zsrc + (q ^ 0) * 16384, q ^ 0, warp, lane, bad & 1u, rph);
                z_repair<1>(acc2, za[1], sb, zsrc + (q ^ 1) * 16384, q ^ 1, warp, lane, bad & 2u, rph);
                z_repair<2>(acc2, za[2], sb, zsrc + (q ^ 2) * 16384, q ^ 2, warp, lane, bad & 4u, rph);
                z_repair<3>(acc2, za[3], sb, zsrc + (q ^ 3) * 16384, q ^ 3, warp, lane, bad & 8u, rph);
            }
        }
        fence_regs(acc2);
        if (threadIdx.x == 0) PROF(10);

        {
            const uint32_t stg = sb + SM_OSTG + warp * 4096;
            const int row = lane & 15;
            const int csel = lane >> 4;
#pragma unroll
            for (int j2 = 0; j2 < 8; j2++) {
                const int j = 2 * j2;
                const uint32_t r0 = pack_bf16(acc2[4 * j + 0], acc2[4 * j + 1]);
                const uint32_t r1 = pack_bf16(acc2[4 * j + 2], acc2[4 * j + 3]);
                const uint32_t r2 = pack_bf16(acc2[4 * j + 4], acc2[4 * j + 5]);
                const uint32_t r3 = pack_bf16(acc2[4 * j + 6], acc2[4 * j + 7]);
                stsm_x4(stg + row * 256 + (((j + csel) ^ (row & 7)) << 4), r0, r1, r2, r3);
            }
            __syncwarp();
            const int tbase = t0 + q * 64 + (warp >> 1) * 32 + (warp & 1) * 4;
            __nv_bfloat16* obase = out + (size_t)batch * T_LEN * D_CH + c4 * 128;
#pragma unroll
            for (int i = 0; i < 8; i++) {
                const int r = 2 * i + (lane >> 4);
                const int ch = lane & 15;
                const int tok = tbase + ((r & 7) >> 1) * 8 + (r >> 3) * 2 + (r & 1);
                uint4 v;
                asm volatile("ld.shared.v4.b32 {%0, %1, %2, %3}, [%4];" : "=r"(v.x), "=r"(v.y), "=r"(v.z), "=r"(v.w)
                             : "r"(stg + r * 256 + ((ch ^ (r & 7)) << 4)) : "memory");
                if (tok < T_LEN) *reinterpret_cast<uint4*>(obase + (size_t)tok * D_CH + ch * 8) = v;
            }
        }
        if (threadIdx.x == 0) PROFG(11);
    }
}

typedef CUresult (*EncodeFn)(CUtensorMap*, CUtensorMapDataType, cuuint32_t, void*, const cuuint64_t*, const cuuint64_t*,
                             const cuuint32_t*, const cuuint32_t*, CUtensorMapInterleave, CUtensorMapSwizzle,
                             CUtensorMapL2promotion, CUtensorMapFloatOOBfill);

void encode(EncodeFn fn, CUtensorMap* m, const void* ptr, int rank, const cuuint64_t* dims, const cuuint64_t* strides,
            const cuuint32_t* box, CUtensorMapSwizzle sw) {
    cuuint32_t es[3] = {1, 1, 1};
    fn(m, CU_TENSOR_MAP_DATA_TYPE_BFLOAT16, rank, const_cast<void*>(ptr), dims, strides, box, es,
       CU_TENSOR_MAP_INTERLEAVE_NONE, sw, CU_TENSOR_MAP_L2_PROMOTION_L2_128B, CU_TENSOR_MAP_FLOAT_OOB_FILL_NONE);
}

}

extern "C" void kernel_launch(void* const* d_in, const int* in_sizes, int n_in, void* d_out, int out_size) {
    (void)in_sizes; (void)n_in; (void)out_size;
    static EncodeFn enc = nullptr;
    if (!enc) {
        void* fn = nullptr;
        cudaDriverEntryPointQueryResult qr;
        cudaGetDriverEntryPoint("cuTensorMapEncodeTiled", &fn, cudaEnableDefault, &qr);
        enc = (EncodeFn)fn;
        cudaFuncSetAttribute(wavenet_fused_kernel, cudaFuncAttributeMaxDynamicSharedMemorySize, SM_TOTAL);
    }
    CUtensorMap mX, mW, mWo;
    {
        cuuint64_t dims[3] = {512, (cuuint64_t)T_LEN, 2}, str[2] = {1024, (cuuint64_t)T_LEN * 1024};
        cuuint32_t box[3] = {64, XBOX, 1};
        encode(enc, &mX, d_in[0], 3, dims, str, box, CU_TENSOR_MAP_SWIZZLE_128B);
    }
    {
        cuuint64_t dims[3] = {512, 2560, 2}, str[2] = {2048, 1024};
        cuuint32_t box[3] = {32, 64, 2};
        encode(enc, &mW, d_in[1], 3, dims, str, box, CU_TENSOR_MAP_SWIZZLE_64B);
    }
    {
        cuuint64_t dims[2] = {512, 512}, str[1] = {1024};
        cuuint32_t box[2] = {64, 64};
        encode(enc, &mWo, d_in[2], 2, dims, str, box, CU_TENSOR_MAP_SWIZZLE_128B);
    }
    wavenet_fused_kernel<<<128, NTHREADS, SM_TOTAL>>>(mX, mW, mWo, (const __nv_bfloat16*)d_in[0], (const __nv_bfloat16*)d_in[1],
                                                    (__nv_bfloat16*)d_out);
}
```

```cpp
#include <cuda_runtime.h>
#include <cuda_bf16.h>
#include <cuda.h>
#include <stdint.h>

namespace {

constexpr int T_LEN   = 1000;
constexpr int D_CH    = 512;
constexpr int NTOK    = 256;
constexpr int XROWS   = NTOK + 8;
constexpr int XBYTES  = XROWS * 128;
constexpr int XBOX    = 88;
constexpr int XST     = 2;
constexpr int WST     = 4;
constexpr int WBYTES  = 8192;
constexpr int WO_BYTES = 131072;

constexpr int SM_WO   = 0;
constexpr int SM_X    = SM_WO + WO_BYTES;
constexpr int SM_W    = SM_X + XST * XBYTES;
constexpr int SM_BAR  = SM_W + WST * WBYTES;
constexpr int SM_TOTAL = SM_BAR + 256;
__host__ __device__ constexpr int sm_zin(int i) { return SM_X + (i >> 1) * XBYTES + (i & 1) * 16384; }
constexpr int SM_OSTG  = SM_W;

constexpr int BAR_WFULL  = 0;
constexpr int BAR_WEMPTY = BAR_WFULL + WST;
constexpr int BAR_XFULL  = BAR_WEMPTY + WST;
constexpr int BAR_XEMPTY = BAR_XFULL + XST;
constexpr int BAR_WO     = BAR_XEMPTY + XST;
constexpr int BAR_PAR    = BAR_WO + 1;
constexpr int BAR_Z      = BAR_PAR + 1;
constexpr int BAR_RETRY  = BAR_Z + 4;

constexpr int SM_PAR   = SM_BAR + 240;
constexpr int NTHREADS = 192;
#define ZDELAY0 900
#define ZDELAY1 600
#define ZDELAY2 550
#define ZDELAY3 550

__device__ uint4 g_zx[2][8 * 4 * 4096];
__device__ unsigned int g_ticket;

#define PROF(i)
#define PROFG(i)

__device__ __forceinline__ uint32_t smem_u32(const void* p) { return (uint32_t)__cvta_generic_to_shared(p); }

__device__ __forceinline__ void mbar_init(uint32_t bar, uint32_t cnt) {
    asm volatile("mbarrier.init.shared::cta.b64 [%0], %1;" ::"r"(bar), "r"(cnt));
}
__device__ __forceinline__ void mbar_expect_tx(uint32_t bar, uint32_t bytes) {
    asm volatile("mbarrier.arrive.expect_tx.shared::cta.b64 _, [%0], %1;" ::"r"(bar), "r"(bytes) : "memory");
}
__device__ __forceinline__ void mbar_arrive(uint32_t bar) {
    asm volatile("mbarrier.arrive.shared::cta.b64 _, [%0];" ::"r"(bar) : "memory");
}
__device__ __forceinline__ void mbar_wait(uint32_t bar, uint32_t parity) {
    asm volatile(
        "{\n"
        ".reg .pred p;\n"
        "WAIT_LOOP:\n"
        "mbarrier.try_wait.parity.shared::cta.b64 p, [%0], %1;\n"
        "@p bra WAIT_DONE;\n"
        "bra WAIT_LOOP;\n"
        "WAIT_DONE:\n"
        "}\n" ::"r"(bar), "r"(parity) : "memory");
}
__device__ __forceinline__ void tma_load_3d(uint32_t dst, const CUtensorMap* m, uint32_t bar, int c0, int c1, int c2) {
    asm volatile("cp.async.bulk.tensor.3d.shared::cluster.global.mbarrier::complete_tx::bytes [%0], [%1, {%3, %4, %5}], [%2];"
                 ::"r"(dst), "l"(m), "r"(bar), "r"(c0), "r"(c1), "r"(c2) : "memory");
}
__device__ __forceinline__ void tma_load_2d(uint32_t dst, const CUtensorMap* m, uint32_t bar, int c0, int c1) {
    asm volatile("cp.async.bulk.tensor.2d.shared::cluster.global.mbarrier::complete_tx::bytes [%0], [%1, {%3, %4}], [%2];"
                 ::"r"(dst), "l"(m), "r"(bar), "r"(c0), "r"(c1) : "memory");
}
__device__ __forceinline__ void fence_proxy_async_smem() { asm volatile("fence.proxy.async.shared::cta;" ::: "memory"); }
__device__ __forceinline__ void prefetch_tmap(const CUtensorMap* m) {
    asm volatile("prefetch.tensormap [%0];" ::"l"(m) : "memory");
}
__device__ __forceinline__ void wgmma_fence() { asm volatile("wgmma.fence.sync.aligned;" ::: "memory"); }
__device__ __forceinline__ void wgmma_commit() { asm volatile("wgmma.commit_group.sync.aligned;" ::: "memory"); }
template <int N> __device__ __forceinline__ void wgmma_wait() {
    asm volatile("wgmma.wait_group.sync.aligned %0;" ::"n"(N) : "memory");
}
template <int N> __device__ __forceinline__ void fence_regs(float (&d)[N]) {
#pragma unroll
    for (int i = 0; i < N; i++) asm volatile("" : "+f"(d[i]) :: "memory");
}
__device__ __forceinline__ void ldsm_x4_trans(uint32_t (&r)[4], uint32_t addr) {
    asm volatile("ldmatrix.sync.aligned.m8n8.x4.trans.shared.b16 {%0, %1, %2, %3}, [%4];"
                 : "=r"(r[0]), "=r"(r[1]), "=r"(r[2]), "=r"(r[3]) : "r"(addr) : "memory");
}
__device__ __forceinline__ void stsm_x4(uint32_t addr, uint32_t a, uint32_t b, uint32_t c, uint32_t d) {
    asm volatile("stmatrix.sync.aligned.m8n8.x4.shared.b16 [%0], {%1, %2, %3, %4};"
                 ::"r"(addr), "r"(a), "r"(b), "r"(c), "r"(d) : "memory");
}
__device__ __forceinline__ void st_relaxed_v4(void* p, uint32_t a, uint32_t b, uint32_t c, uint32_t d) {
    asm volatile("st.relaxed.gpu.global.v4.b32 [%0], {%1, %2, %3, %4};" ::"l"(p), "r"(a), "r"(b), "r"(c), "r"(d) : "memory");
}
__device__ __forceinline__ void bulk_load(uint32_t dst, const void* src, uint32_t bytes, uint32_t bar) {
    asm volatile("cp.async.bulk.shared::cluster.global.mbarrier::complete_tx::bytes [%0], [%1], %2, [%3];"
                 ::"r"(dst), "l"(src), "r"(bytes), "r"(bar) : "memory");
}
__device__ __forceinline__ uint32_t clock_now() {
    uint32_t t;
    asm volatile("mov.u32 %0, %%clock;" : "=r"(t) :: "memory");
    return t;
}
template <int BIT>
__device__ __forceinline__ void sched_fence(uint32_t zero) {
    asm volatile("{\n.reg .pred p;\n.reg .b32 t;\nand.b32 t, %0, %1;\nsetp.eq.u32 p, t, 0;\n@p bra SF_DONE;\ntrap;\nSF_DONE:\n}\n"
                 ::"r"(zero), "n"(1u << BIT) : "memory");
}
__device__ __forceinline__ float tanh_fast(float x) {
    float y;
    asm volatile("tanh.approx.f32 %0, %1;" : "=f"(y) : "f"(x));
    return y;
}
__device__ __forceinline__ void load_w_frags(uint32_t (&f)[4][4], uint32_t wa) {
#pragma unroll
    for (int kk = 0; kk < 4; kk++) ldsm_x4_trans(f[kk], wa + kk * 1024);
}
__device__ __forceinline__ void scale_w_frags(uint32_t (&f)[4][4]) {
#pragma unroll
    for (int kk = 0; kk < 4; kk++) {
        asm volatile("mul.rn.bf16x2 %0, %0, %1;" : "+r"(f[kk][1]) : "r"(0x3F003F00u));
        asm volatile("mul.rn.bf16x2 %0, %0, %1;" : "+r"(f[kk][3]) : "r"(0x3F003F00u));
    }
}
__device__ __forceinline__ uint32_t pack_bf16(float lo, float hi) {
    uint32_t r;
    asm("cvt.rn.bf16x2.f32 %0, %1, %2;" : "=r"(r) : "f"(hi), "f"(lo));
    return r;
}
__device__ __forceinline__ uint64_t make_desc(uint32_t addr, uint32_t lbo_bytes, uint32_t sbo_bytes) {
    return (uint64_t)((addr & 0x3FFFF) >> 4) | ((uint64_t)(lbo_bytes >> 4) << 16) | ((uint64_t)(sbo_bytes >> 4) << 32) |
           ((uint64_t)1 << 62);
}

#define R8(d, o) "+f"(d[o + 0]), "+f"(d[o + 1]), "+f"(d[o + 2]), "+f"(d[o + 3]), "+f"(d[o + 4]), "+f"(d[o + 5]), "+f"(d[o + 6]), "+f"(d[o + 7])

__device__ __forceinline__ void wgmma_m64n128k16_rs(float (&d)[64], const uint32_t (&a)[4], uint64_t descB) {
    asm volatile(
        "wgmma.mma_async.sync.aligned.m64n128k16.f32.bf16.bf16 "
        "{%0, %1, %2, %3, %4, %5, %6, %7, %8, %9, %10, %11, %12, %13, %14, %15, "
        "%16, %17, %18, %19, %20, %21, %22, %23, %24, %25, %26, %27, %28, %29, %30, %31, "
        "%32, %33, %34, %35, %36, %37, %38, %39, %40, %41, %42, %43, %44, %45, %46, %47, "
        "%48, %49, %50, %51, %52, %53, %54, %55, %56, %57, %58, %59, %60, %61, %62, %63}, "
        "{%64, %65, %66, %67}, %68, 1, -1, 1, 1;\n"
        : R8(d, 0), R8(d, 8), R8(d, 16), R8(d, 24), R8(d, 32), R8(d, 40), R8(d, 48), R8(d, 56)
        : "r"(a[0]), "r"(a[1]), "r"(a[2]), "r"(a[3]), "l"(descB));
}

template <int OFF>
__device__ __forceinline__ void wgmma_m64n128k16_rs_half(float (&d)[128], const uint32_t (&a)[4], uint64_t descB) {
    asm volatile(
        "wgmma.mma_async.sync.aligned.m64n128k16.f32.bf16.bf16 "
        "{%0, %1, %2, %3, %4, %5, %6, %7, %8, %9, %10, %11, %12, %13, %14, %15, "
        "%16, %17, %18, %19, %20, %21, %22, %23, %24, %25, %26, %27, %28, %29, %30, %31, "
        "%32, %33, %34, %35, %36, %37, %38, %39, %40, %41, %42, %43, %44, %45, %46, %47, "
        "%48, %49, %50, %51, %52, %53, %54, %55, %56, %57, %58, %59, %60, %61, %62, %63}, "
        "{%64, %65, %66, %67}, %68, 1, 1, 1, 0;\n"
        : R8(d, OFF + 0), R8(d, OFF + 8), R8(d, OFF + 16), R8(d, OFF + 24), R8(d, OFF + 32), R8(d, OFF + 40), R8(d, OFF + 48), R8(d, OFF + 56)
        : "r"(a[0]), "r"(a[1]), "r"(a[2]), "r"(a[3]), "l"(descB));
}
template <int OFF> __device__ __forceinline__ void fence_half(float (&d)[128]) {
#pragma unroll
    for (int i = 0; i < 64; i++) asm volatile("" : "+f"(d[OFF + i]) :: "memory");
}

template <int Q0, int N> struct GateGroup { static constexpr int J = 2 * (Q0 ^ (N >> 1)) + (N & 1); };

template <int Q0, int N>
__device__ __forceinline__ void gate_mufu(float (&acc)[128]) {
    constexpr int J = GateGroup<Q0, N>::J;
#pragma unroll
    for (int i = 0; i < 16; i++) acc[16 * J + i] = tanh_fast(acc[16 * J + i]);
}
template <int Q0, int N>
__device__ __forceinline__ void gate_finish(float (&acc)[128], uint8_t* zdst) {
    constexpr int J = GateGroup<Q0, N>::J;
    uint32_t zp[4];
#pragma unroll
    for (int i = 0; i < 4; i++) {
        const int r = 16 * J + 4 * i;
        zp[i] = __vmaxu2(pack_bf16(acc[r] * fmaf(acc[r + 2], -0.5f, -0.5f), acc[r + 1] * fmaf(acc[r + 3], -0.5f, -0.5f)), 0x00010001u);
    }
    st_relaxed_v4(zdst + (J >> 1) * 65536 + (J & 1) * 8192, zp[0], zp[1], zp[2], zp[3]);
    if (N & 1) asm volatile("bar.arrive %0, 160;" ::"n"(2 + (N >> 1)) : "memory");
}

template <int Q0>
__device__ __forceinline__ void tail_gemm1(float (&acc)[128], uint32_t (&afr)[2][4][4], uint32_t sb, int ws, int wph, uint32_t a_lane_off,
                                           uint8_t* zdst, int lane, uint32_t zero) {
    constexpr int OA = (Q0 >> 1) * 64;
    constexpr int OB = 64 - OA;
    const uint32_t bars = sb + SM_BAR;
    uint32_t keep[4][4], ext[4][4];
    const int ws0 = ws;
    auto wtile = [&](int tap) { return sb + SM_W + ((ws0 + tap) & (WST - 1)) * WBYTES + a_lane_off; };
    auto wwait = [&](int tap) {
        const int st = ws0 + tap;
        mbar_wait(bars + 8 * (BAR_WFULL + (st & (WST - 1))), wph ^ ((st >> 2) & 1));
    };
    auto load = [&](uint32_t (&f)[4][4], int tap) { load_w_frags(f, wtile(tap)); };
    auto issueA = [&](uint32_t (&f)[4][4], int tap) {
        const uint64_t db = make_desc(sb + SM_X + XBYTES + (8 - 2 * tap) * 128 + OA * 256, 16, 1024);
        wgmma_fence();
#pragma unroll
        for (int kk = 0; kk < 4; kk++) wgmma_m64n128k16_rs_half<OA>(acc, f[kk], db + kk * 2);
        wgmma_commit();
    };
    auto issueB = [&](uint32_t (&f)[4][4], int tap) {
        const uint64_t db = make_desc(sb + SM_X + XBYTES + (8 - 2 * tap) * 128 + OB * 256, 16, 1024);
        wgmma_fence();
#pragma unroll
        for (int kk = 0; kk < 4; kk++) wgmma_m64n128k16_rs_half<OB>(acc, f[kk], db + kk * 2);
        wgmma_commit();
    };
    mbar_wait(bars + 8 * (BAR_XFULL + 1), 1);
    wwait(0); load(keep, 0);
    __syncwarp();
    if (lane == 0) mbar_arrive(bars + 8 * (BAR_WEMPTY + ws0));
    wwait(1); load(afr[1], 1);
    wwait(2); load(ext, 2);
    scale_w_frags(keep);   issueA(keep, 0);   wgmma_wait<1>();
    wwait(3); load(afr[0], 3);
    scale_w_frags(afr[1]); issueA(afr[1], 1); wgmma_wait<1>();
    scale_w_frags(ext);    issueA(ext, 2);    wgmma_wait<1>();
    wwait(4); load(afr[1], 4);
    scale_w_frags(afr[0]); issueA(afr[0], 3); wgmma_wait<1>();
    scale_w_frags(afr[1]); issueA(afr[1], 4); wgmma_wait<1>();
    if (threadIdx.x == 0) PROF(24);
    issueB(keep, 0);
    issueB(ext, 2);
    wgmma_wait<2>();
    fence_half<OA>(acc);
    sched_fence<0>(zero);
    gate_mufu<Q0, 0>(acc); gate_mufu<Q0, 1>(acc);
    gate_finish<Q0, 0>(acc, zdst); gate_finish<Q0, 1>(acc, zdst);
    sched_fence<1>(zero);
    issueB(afr[0], 3);
    issueB(afr[1], 4);
    wgmma_wait<2>();
    load(keep, 1);
    sched_fence<2>(zero);
    gate_mufu<Q0, 2>(acc);
    sched_fence<3>(zero);
    scale_w_frags(keep);
    issueB(keep, 1);
    sched_fence<4>(zero);
    gate_mufu<Q0, 3>(acc);
    gate_finish<Q0, 2>(acc, zdst); gate_finish<Q0, 3>(acc, zdst);
    wgmma_wait<0>();
    fence_half<OB>(acc);
    if (threadIdx.x == 0) PROF(3);
    gate_mufu<Q0, 4>(acc);
    gate_mufu<Q0, 5>(acc);
    gate_finish<Q0, 4>(acc, zdst);
    gate_mufu<Q0, 6>(acc);
    gate_finish<Q0, 5>(acc, zdst);
    gate_mufu<Q0, 7>(acc);
    gate_finish<Q0, 6>(acc, zdst);
    gate_finish<Q0, 7>(acc, zdst);
}

__device__ __forceinline__ void fetch_slot(int i, uint32_t sb, const uint8_t* zsrc, int q, int lane) {
    const uint32_t bars = sb + SM_BAR;
    asm volatile("bar.sync %0, 160;" ::"r"(2 + i) : "memory");
    const uint32_t t = clock_now();
    if (lane == 0) {
        while (clock_now() - t < (uint32_t)(i == 0 ? ZDELAY0 : i == 1 ? ZDELAY1 : i == 2 ? ZDELAY2 : ZDELAY3)) {}
        mbar_expect_tx(bars + 8 * (BAR_Z + i), 16384);
        bulk_load(sb + sm_zin(i), zsrc + (q ^ i) * 16384, 16384, bars + 8 * (BAR_Z + i));
        PROF(26 + i);
    }
    __syncwarp();
}

template <int I>
__device__ __forceinline__ void z_load(uint32_t (&z)[8][4], uint32_t sb, int warp, int lane) {
    mbar_wait(sb + SM_BAR + 8 * (BAR_Z + I), 0);
#pragma unroll
    for (int j = 0; j < 8; j++) ldsm_x4_trans(z[j], sb + sm_zin(I) + warp * 4096 + j * 512 + lane * 16);
}
__device__ __forceinline__ bool z_check(const uint32_t (&z)[8][4]) {
    uint32_t m0 = 0xFFFFFFFFu, m1 = 0xFFFFFFFFu;
#pragma unroll
    for (int j = 0; j < 8; j++) {
        m0 = __vimin3_u16x2(m0, z[j][0], z[j][1]);
        m1 = __vimin3_u16x2(m1, z[j][2], z[j][3]);
    }
    m0 = __vminu2(m0, m1);
    return __all_sync(0xffffffffu, ((m0 & 0xFFFFu) != 0u) && ((m0 >> 16) != 0u));
}
__device__ __forceinline__ void z_issue(float (&acc2)[64], uint32_t (&z)[8][4], uint32_t sb, int beta) {
#pragma unroll
    for (int j = 0; j < 8; j++) asm volatile("" : "+r"(z[j][0]), "+r"(z[j][1]), "+r"(z[j][2]), "+r"(z[j][3]) :: "memory");
    const uint64_t db = make_desc(sb + SM_WO + beta * 16384, 65536, 1024);
    wgmma_fence();
#pragma unroll
    for (int j = 0; j < 8; j++) wgmma_m64n128k16_rs(acc2, z[j], db + j * 128);
    wgmma_commit();
}
__device__ __forceinline__ bool wg_any(bool p) {
    uint32_t r;
    asm volatile("{\n.reg .pred a, b;\nsetp.ne.u32 a, %1, 0;\nbarrier.cta.red.or.aligned.pred b, 1, 128, a;\nselp.u32 %0, 1, 0, b;\n}\n"
                 : "=r"(r) : "r"((uint32_t)p) : "memory");
    return r != 0;
}
template <int I>
__device__ __forceinline__ void z_repair(float (&acc2)[64], uint32_t (&z)[8][4], uint32_t sb, const uint8_t* src, int beta, int warp,
                                         int lane, uint32_t mine, uint32_t& rph) {
    if (!wg_any(mine != 0u)) return;
    if (mine) {
        const uint32_t zs = sb + sm_zin(I) + warp * 4096;
        const uint32_t bar = sb + SM_BAR + 8 * (BAR_RETRY + warp);
        uint32_t zn[8][4];
        int spins = 0;
        do {
            __syncwarp();
            if (lane == 0) {
                mbar_expect_tx(bar, 4096);
                bulk_load(zs, src, 4096, bar);
            }
            mbar_wait(bar, rph);
            rph ^= 1;
#pragma unroll
            for (int j = 0; j < 8; j++) ldsm_x4_trans(zn[j], zs + j * 512 + lane * 16);
        } while (!z_check(zn) && ++spins < (1 << 16));
#pragma unroll
        for (int j = 0; j < 8; j++)
#pragma unroll
            for (int k = 0; k < 4; k++) z[j][k] = zn[j][k] & __vcmpeq2(z[j][k], 0u);
    } else {
#pragma unroll
        for (int j = 0; j < 8; j++)
#pragma unroll
            for (int k = 0; k < 4; k++) z[j][k] = 0u;
    }
    z_issue(acc2, z, sb, beta);
    wgmma_wait<0>();
}

__global__ void __launch_bounds__(NTHREADS, 1)
wavenet_fused_kernel(const __grid_constant__ CUtensorMap mapX, const __grid_constant__ CUtensorMap mapW,
                     const __grid_constant__ CUtensorMap mapWo, __nv_bfloat16* __restrict__ out, const uint32_t zero) {
    extern __shared__ __align__(1024) uint8_t smem_raw[];
    const uint32_t sb = smem_u32(smem_raw);
    const uint32_t bars = sb + SM_BAR;
    const int warp = threadIdx.x >> 5;
    const int lane = threadIdx.x & 31;
    const int cg = blockIdx.x & 15;
    const int tt = blockIdx.x >> 4;
    const int batch = tt >> 2;
    const int t0 = (tt & 3) * NTOK;
    const int c4 = cg & 3, q = cg >> 2;

    if (threadIdx.x == 160) {
        prefetch_tmap(&mapW);
        prefetch_tmap(&mapX);
    }
    if (threadIdx.x == 128) {
        PROFG(0);
        const uint32_t xf = bars + 8 * BAR_XFULL;
        mbar_init(xf, 1);
        mbar_init(bars + 8 * BAR_WFULL, 1);
        asm volatile("fence.mbarrier_init.release.cluster;" ::: "memory");
        fence_proxy_async_smem();
        mbar_expect_tx(bars + 8 * BAR_WFULL, WBYTES);
        tma_load_3d(sb + SM_W, &mapW, bars + 8 * BAR_WFULL, cg * 32, 0, 0);
        mbar_expect_tx(xf, XBYTES);
#pragma unroll
        for (int j = 0; j < 3; j++) tma_load_3d(sb + SM_X + j * XBOX * 128, &mapX, xf, 0, t0 - 8 + j * XBOX, batch);
        for (int i = 1; i < WST; i++) mbar_init(bars + 8 * (BAR_WFULL + i), 1);
        asm volatile("fence.mbarrier_init.release.cluster;" ::: "memory");
        fence_proxy_async_smem();
#pragma unroll
        for (int i = 1; i < WST; i++) {
            mbar_expect_tx(bars + 8 * (BAR_WFULL + i), WBYTES);
            tma_load_3d(sb + SM_W + i * WBYTES, &mapW, bars + 8 * (BAR_WFULL + i), cg * 32, i * 512, 0);
        }
    } else if (threadIdx.x == 0) {
        for (int i = 0; i < WST; i++) mbar_init(bars + 8 * (BAR_WEMPTY + i), 4);
        mbar_init(bars + 8 * (BAR_XFULL + 1), 1);
        for (int i = 0; i < XST; i++) mbar_init(bars + 8 * (BAR_XEMPTY + i), 4);
        mbar_init(bars + 8 * BAR_WO, 1);
        mbar_init(bars + 8 * BAR_PAR, 1);
        for (int i = 0; i < 4; i++) {
            mbar_init(bars + 8 * (BAR_Z + i), 1);
            mbar_init(bars + 8 * (BAR_RETRY + i), 1);
        }
        asm volatile("fence.mbarrier_init.release.cluster;" ::: "memory");
    }
    __syncthreads();

    if (warp >= 4) {
        if (warp == 4) {
            if (lane == 0) {
                int ws = 0, wph = 0;
                for (int kc = 0; kc < 8; kc++) {
                    const int xs = kc & 1;
                    if (kc > 0) {
                        mbar_wait(bars + 8 * (BAR_XEMPTY + xs), ((kc >> 1) & 1) ^ 1);
                        const uint32_t xf = bars + 8 * (BAR_XFULL + xs);
                        mbar_expect_tx(xf, XBYTES);
                        const uint32_t xd = sb + SM_X + xs * XBYTES;
#pragma unroll
                        for (int j = 0; j < 3; j++) tma_load_3d(xd + j * XBOX * 128, &mapX, xf, kc * 64, t0 - 8 + j * XBOX, batch);
                    } else {
                        prefetch_tmap(&mapWo);
                    }
                    for (int tap = (kc == 0 ? WST : 0); tap < 5; tap++) {
                        mbar_wait(bars + 8 * (BAR_WEMPTY + ws), wph);
                        const uint32_t wf = bars + 8 * (BAR_WFULL + ws);
                        mbar_expect_tx(wf, WBYTES);
                        tma_load_3d(sb + SM_W + ws * WBYTES, &mapW, wf, cg * 32, tap * 512 + kc * 64, 0);
                        if (++ws == WST) { ws = 0; wph ^= 1; }
                        const int it = kc * 5 + tap - 10;
                        if (it >= 0 && it < 16) {
                            const uint32_t wob = bars + 8 * BAR_WO;
                            if (it == 0) mbar_expect_tx(wob, WO_BYTES);
                            tma_load_2d(sb + SM_WO + (it & 1) * 65536 + (it >> 1) * 8192, &mapWo, wob, c4 * 128 + (it & 1) * 64, (it >> 1) * 64);
                        }
                    }
                }
            }
            __syncwarp();
        } else {
            unsigned int par = 0;
            if (lane == 0) par = (atomicAdd(&g_ticket, 1u) >> 7) & 1u;
            par = __shfl_sync(0xffffffffu, par, 0);
            __nanosleep(1500);
            uint4* mine = &g_zx[par][tt * 4 * 4096 + q * 1024 + 2 * c4 * 32];
#pragma unroll 1
            for (int i = 0; i < 32; i++) {
                mine[(i >> 3) * 4096 + ((i >> 1) & 3) * 256 + (i & 1) * 32 + lane] = make_uint4(0u, 0u, 0u, 0u);
                __nanosleep(100);
            }
            __syncwarp();
            if (lane == 0) {
                asm volatile("st.shared.u32 [%0], %1;" ::"r"(sb + SM_PAR), "r"(par) : "memory");
                mbar_arrive(bars + 8 * BAR_PAR);
            }
            uint4* clr = &g_zx[par ^ 1][blockIdx.x * 1024];
#pragma unroll 1
            for (int i = 0; i < 32; i++) {
                clr[i * 32 + lane] = make_uint4(0u, 0u, 0u, 0u);
                __nanosleep(100);
            }
        }
        mbar_wait(bars + 8 * BAR_PAR, 0);
        uint32_t par;
        asm volatile("ld.shared.u32 %0, [%1];" : "=r"(par) : "r"(sb + SM_PAR) : "memory");
        const uint8_t* zsrc = reinterpret_cast<const uint8_t*>(&g_zx[par][(tt * 4 + q) * 4096]);
        fetch_slot(5 - warp, sb, zsrc, q, lane);
        fetch_slot(7 - warp, sb, zsrc, q, lane);
    } else {
        float acc[128];
#pragma unroll
        for (int i = 0; i < 128; i++) acc[i] = 0.f;
        uint32_t afr[2][4][4];
        const int lk = ((lane >> 4) << 3) + (lane & 7);
        const uint32_t a_lane_off = ((lane >> 3) & 1) * 4096 + lk * 64 + ((warp ^ ((lk >> 1) & 3)) << 4);
        int ws = 0, wph = 0;
        uint32_t par = 0;
        if (threadIdx.x == 0) PROF(1);
#pragma unroll 1
        for (int kc2 = 0; kc2 < 4; kc2++) {
#pragma unroll
            for (int u = 0; u < 10; u++) {
                const int xs = u / 5;
                const int tap = u % 5;
                if (u == 5 && kc2 == 3) break;
                if (tap == 0) mbar_wait(bars + 8 * (BAR_XFULL + xs), kc2 & 1);
                mbar_wait(bars + 8 * (BAR_WFULL + ws), wph);
                if (kc2 == 0 && u == 0 && threadIdx.x == 0) PROF(2);
                const uint32_t wa = sb + SM_W + ws * WBYTES + a_lane_off;
                load_w_frags(afr[u & 1], wa);
                __syncwarp();
                if (lane == 0) mbar_arrive(bars + 8 * (BAR_WEMPTY + ws));
                scale_w_frags(afr[u & 1]);
                if (++ws == WST) { ws = 0; wph ^= 1; }
                const uint64_t db = make_desc(sb + SM_X + xs * XBYTES + (8 - 2 * tap) * 128, 16, 1024);
                wgmma_fence();
#pragma unroll
                for (int kk = 0; kk < 4; kk++) {
                    wgmma_m64n128k16_rs_half<0>(acc, afr[u & 1][kk], db + kk * 2);
                    wgmma_m64n128k16_rs_half<64>(acc, afr[u & 1][kk], db + kk * 2 + 1024);
                }
                wgmma_commit();
                if (u == 2 && kc2 == 3) {
                    mbar_wait(bars + 8 * BAR_PAR, 0);
                    asm volatile("ld.shared.u32 %0, [%1];" : "=r"(par) : "r"(sb + SM_PAR) : "memory");
                    mbar_wait(bars + 8 * BAR_WO, 0);
                }
                wgmma_wait<1>();
                if (tap == 0 && (u > 0 || kc2 > 0)) {
                    if (lane == 0) mbar_arrive(bars + 8 * (BAR_XEMPTY + (xs ^ 1)));
                }
            }
        }
        uint8_t* zx = reinterpret_cast<uint8_t*>(&g_zx[par][tt * 4 * 4096]);
        uint8_t* zdst = zx + q * 16384 + (2 * c4 + (warp >> 1)) * 512 + (warp & 1) * 256 +
                        ((lane >> 1) & 1) * 4096 + (lane & 1) * 128 + (lane >> 2) * 16;
        switch (q) {
            case 0: tail_gemm1<0>(acc, afr, sb, ws, wph, a_lane_off, zdst, lane, zero); break;
            case 1: tail_gemm1<1>(acc, afr, sb, ws, wph, a_lane_off, zdst, lane, zero); break;
            case 2: tail_gemm1<2>(acc, afr, sb, ws, wph, a_lane_off, zdst, lane, zero); break;
            default: tail_gemm1<3>(acc, afr, sb, ws, wph, a_lane_off, zdst, lane, zero); break;
        }
        if (threadIdx.x == 0) PROF(4);

        float acc2[64];
#pragma unroll
        for (int i = 0; i < 64; i++) acc2[i] = 0.f;
        {
            uint32_t za[4][8][4];
            uint32_t bad;
            z_load<0>(za[0], sb, warp, lane);
            if (threadIdx.x == 0) PROF(12);
            z_issue(acc2, za[0], sb, q ^ 0);
            z_load<1>(za[1], sb, warp, lane);
            bad = z_check(za[0]) ? 0u : 1u;
            if (threadIdx.x == 0) PROF(13);
            z_issue(acc2, za[1], sb, q ^ 1);
            z_load<2>(za[2], sb, warp, lane);
            bad |= z_check(za[1]) ? 0u : 2u;
            if (threadIdx.x == 0) PROF(14);
            z_issue(acc2, za[2], sb, q ^ 2);
            z_load<3>(za[3], sb, warp, lane);
            bad |= z_check(za[2]) ? 0u : 4u;
            if (threadIdx.x == 0) PROF(15);
            z_issue(acc2, za[3], sb, q ^ 3);
            bad |= z_check(za[3]) ? 0u : 8u;
            const bool any_bad = wg_any(bad != 0u);
            wgmma_wait<0>();
            if (__builtin_expect(any_bad, 0)) {
                const uint8_t* zsrc = zx + q * 65536 + warp * 4096;
                uint32_t rph = 0;
                z_repair<0>(acc2, za[0], sb, zsrc + (q ^ 0) * 16384, q ^ 0, warp, lane, bad & 1u, rph);
                z_repair<1>(acc2, za[1], sb, zsrc + (q ^ 1) * 16384, q ^ 1, warp, lane, bad & 2u, rph);
                z_repair<2>(acc2, za[2], sb, zsrc + (q ^ 2) * 16384, q ^ 2, warp, lane, bad & 4u, rph);
                z_repair<3>(acc2, za[3], sb, zsrc + (q ^ 3) * 16384, q ^ 3, warp, lane, bad & 8u, rph);
            }
        }
        fence_regs(acc2);
        if (threadIdx.x == 0) PROF(10);

        {
            const uint32_t stg = sb + SM_OSTG + warp * 4096;
            const int row = lane & 15;
            const int csel = lane >> 4;
#pragma unroll
            for (int j2 = 0; j2 < 8; j2++) {
                const int j = 2 * j2;
                const uint32_t r0 = pack_bf16(acc2[4 * j + 0], acc2[4 * j + 1]);
                const uint32_t r1 = pack_bf16(acc2[4 * j + 2], acc2[4 * j + 3]);
                const uint32_t r2 = pack_bf16(acc2[4 * j + 4], acc2[4 * j + 5]);
                const uint32_t r3 = pack_bf16(acc2[4 * j + 6], acc2[4 * j + 7]);
                stsm_x4(stg + row * 256 + (((j + csel) ^ (row & 7)) << 4), r0, r1, r2, r3);
            }
            __syncwarp();
            const int tbase = t0 + q * 64 + (warp >> 1) * 32 + (warp & 1) * 4;
            __nv_bfloat16* obase = out + (size_t)batch * T_LEN * D_CH + c4 * 128;
#pragma unroll
            for (int i = 0; i < 8; i++) {
                const int r = 2 * i + (lane >> 4);
                const int ch = lane & 15;
                const int tok = tbase + ((r & 7) >> 1) * 8 + (r >> 3) * 2 + (r & 1);
                uint4 v;
                asm volatile("ld.shared.v4.b32 {%0, %1, %2, %3}, [%4];" : "=r"(v.x), "=r"(v.y), "=r"(v.z), "=r"(v.w)
                             : "r"(stg + r * 256 + ((ch ^ (r & 7)) << 4)) : "memory");
                if (tok < T_LEN) *reinterpret_cast<uint4*>(obase + (size_t)tok * D_CH + ch * 8) = v;
            }
        }
        if (threadIdx.x == 0) PROFG(11);
    }
}

typedef CUresult (*EncodeFn)(CUtensorMap*, CUtensorMapDataType, cuuint32_t, void*, const cuuint64_t*, const cuuint64_t*,
                             const cuuint32_t*, const cuuint32_t*, CUtensorMapInterleave, CUtensorMapSwizzle,
                             CUtensorMapL2promotion, CUtensorMapFloatOOBfill);

void encode(EncodeFn fn, CUtensorMap* m, const void* ptr, int rank, const cuuint64_t* dims, const cuuint64_t* strides,
            const cuuint32_t* box, CUtensorMapSwizzle sw) {
    cuuint32_t es[3] = {1, 1, 1};
    fn(m, CU_TENSOR_MAP_DATA_TYPE_BFLOAT16, rank, const_cast<void*>(ptr), dims, strides, box, es,
       CU_TENSOR_MAP_INTERLEAVE_NONE, sw, CU_TENSOR_MAP_L2_PROMOTION_L2_128B, CU_TENSOR_MAP_FLOAT_OOB_FILL_NONE);
}

}

extern "C" void kernel_launch(void* const* d_in, const int* in_sizes, int n_in, void* d_out, int out_size) {
    (void)in_sizes; (void)n_in; (void)out_size;
    static EncodeFn enc = nullptr;
    if (!enc) {
        void* fn = nullptr;
        cudaDriverEntryPointQueryResult qr;
        cudaGetDriverEntryPoint("cuTensorMapEncodeTiled", &fn, cudaEnableDefault, &qr);
        enc = (EncodeFn)fn;
        cudaFuncSetAttribute(wavenet_fused_kernel, cudaFuncAttributeMaxDynamicSharedMemorySize, SM_TOTAL);
    }
    CUtensorMap mX, mW, mWo;
    {
        cuuint64_t dims[3] = {512, (cuuint64_t)T_LEN, 2}, str[2] = {1024, (cuuint64_t)T_LEN * 1024};
        cuuint32_t box[3] = {64, XBOX, 1};
        encode(enc, &mX, d_in[0], 3, dims, str, box, CU_TENSOR_MAP_SWIZZLE_128B);
    }
    {
        cuuint64_t dims[3] = {512, 2560, 2}, str[2] = {2048, 1024};
        cuuint32_t box[3] = {32, 64, 2};
        encode(enc, &mW, d_in[1], 3, dims, str, box, CU_TENSOR_MAP_SWIZZLE_64B);
    }
    {
        cuuint64_t dims[2] = {512, 512}, str[1] = {1024};
        cuuint32_t box[2] = {64, 64};
        encode(enc, &mWo, d_in[2], 2, dims, str, box, CU_TENSOR_MAP_SWIZZLE_128B);
    }
    wavenet_fused_kernel<<<128, NTHREADS, SM_TOTAL>>>(mX, mW, mWo, (__nv_bfloat16*)d_out, 0u);
}
```

```cpp
#include <cuda_runtime.h>
#include <cuda_bf16.h>
#include <cuda.h>
#include <stdint.h>

namespace {

constexpr int T_LEN   = 1000;
constexpr int D_CH    = 512;
constexpr int NTOK    = 256;
constexpr int XROWS   = NTOK + 8;
constexpr int XBYTES  = XROWS * 128;
constexpr int XBOX    = 88;
constexpr int XST     = 2;
constexpr int WST     = 4;
constexpr int WBYTES  = 8192;
constexpr int WO_BYTES = 131072;

constexpr int SM_WO   = 0;
constexpr int SM_X    = SM_WO + WO_BYTES;
constexpr int SM_W    = SM_X + XST * XBYTES;
constexpr int SM_BAR  = SM_W + WST * WBYTES;
constexpr int SM_TOTAL = SM_BAR + 256;
__host__ __device__ constexpr int sm_zin(int i) { return SM_X + (i >> 1) * XBYTES + (i & 1) * 16384; }
constexpr int SM_OSTG  = SM_W;
constexpr int SM_ZFIX  = SM_W + 16384;

constexpr int BAR_WFULL  = 0;
constexpr int BAR_WEMPTY = BAR_WFULL + WST;
constexpr int BAR_XFULL  = BAR_WEMPTY + WST;
constexpr int BAR_XEMPTY = BAR_XFULL + XST;
constexpr int BAR_WO     = BAR_XEMPTY + XST;
constexpr int BAR_PAR    = BAR_WO + 1;
constexpr int BAR_Z      = BAR_PAR + 1;
constexpr int BAR_RETRY  = BAR_Z + 4;

constexpr int SM_PAR   = SM_BAR + 240;
constexpr int NTHREADS = 256;
#define GB 4
#define PB 0
#define G2O 0
#define G2F 1
#define ZDELAY0 600
#define ZDELAY1 450
#define ZDELAY2 500
#define ZDELAY3 500

__device__ uint4 g_zx[2][8 * 4 * 4096];
__device__ unsigned int g_ticket;

#define PROF(i)
#define PROFG(i)

__device__ __forceinline__ uint32_t smem_u32(const void* p) { return (uint32_t)__cvta_generic_to_shared(p); }

__device__ __forceinline__ void mbar_init(uint32_t bar, uint32_t cnt) {
    asm volatile("mbarrier.init.shared::cta.b64 [%0], %1;" ::"r"(bar), "r"(cnt));
}
__device__ __forceinline__ void mbar_expect_tx(uint32_t bar, uint32_t bytes) {
    asm volatile("mbarrier.arrive.expect_tx.shared::cta.b64 _, [%0], %1;" ::"r"(bar), "r"(bytes) : "memory");
}
__device__ __forceinline__ void mbar_arrive(uint32_t bar) {
    asm volatile("mbarrier.arrive.shared::cta.b64 _, [%0];" ::"r"(bar) : "memory");
}
__device__ __forceinline__ void mbar_wait(uint32_t bar, uint32_t parity) {
    asm volatile(
        "{\n"
        ".reg .pred p;\n"
        "WAIT_LOOP:\n"
        "mbarrier.try_wait.parity.shared::cta.b64 p, [%0], %1;\n"
        "@p bra WAIT_DONE;\n"
        "bra WAIT_LOOP;\n"
        "WAIT_DONE:\n"
        "}\n" ::"r"(bar), "r"(parity) : "memory");
}
__device__ __forceinline__ void tma_load_3d(uint32_t dst, const CUtensorMap* m, uint32_t bar, int c0, int c1, int c2) {
    asm volatile("cp.async.bulk.tensor.3d.shared::cluster.global.mbarrier::complete_tx::bytes [%0], [%1, {%3, %4, %5}], [%2];"
                 ::"r"(dst), "l"(m), "r"(bar), "r"(c0), "r"(c1), "r"(c2) : "memory");
}
__device__ __forceinline__ void tma_load_2d(uint32_t dst, const CUtensorMap* m, uint32_t bar, int c0, int c1) {
    asm volatile("cp.async.bulk.tensor.2d.shared::cluster.global.mbarrier::complete_tx::bytes [%0], [%1, {%3, %4}], [%2];"
                 ::"r"(dst), "l"(m), "r"(bar), "r"(c0), "r"(c1) : "memory");
}
__device__ __forceinline__ void fence_proxy_async_smem() { asm volatile("fence.proxy.async.shared::cta;" ::: "memory"); }
__device__ __forceinline__ void prefetch_tmap(const CUtensorMap* m) {
    asm volatile("prefetch.tensormap [%0];" ::"l"(m) : "memory");
}
__device__ __forceinline__ void wgmma_fence() { asm volatile("wgmma.fence.sync.aligned;" ::: "memory"); }
__device__ __forceinline__ void wgmma_commit() { asm volatile("wgmma.commit_group.sync.aligned;" ::: "memory"); }
template <int N> __device__ __forceinline__ void wgmma_wait() {
    asm volatile("wgmma.wait_group.sync.aligned %0;" ::"n"(N) : "memory");
}
template <int N> __device__ __forceinline__ void fence_regs(float (&d)[N]) {
#pragma unroll
    for (int i = 0; i < N; i++) asm volatile("" : "+f"(d[i]) :: "memory");
}
__device__ __forceinline__ void ldsm_x4_trans(uint32_t (&r)[4], uint32_t addr) {
    asm volatile("ldmatrix.sync.aligned.m8n8.x4.trans.shared.b16 {%0, %1, %2, %3}, [%4];"
                 : "=r"(r[0]), "=r"(r[1]), "=r"(r[2]), "=r"(r[3]) : "r"(addr) : "memory");
}
__device__ __forceinline__ void stsm_x4(uint32_t addr, uint32_t a, uint32_t b, uint32_t c, uint32_t d) {
    asm volatile("stmatrix.sync.aligned.m8n8.x4.shared.b16 [%0], {%1, %2, %3, %4};"
                 ::"r"(addr), "r"(a), "r"(b), "r"(c), "r"(d) : "memory");
}
__device__ __forceinline__ void st_relaxed_v4(void* p, uint32_t a, uint32_t b, uint32_t c, uint32_t d) {
    asm volatile("st.relaxed.gpu.global.v4.b32 [%0], {%1, %2, %3, %4};" ::"l"(p), "r"(a), "r"(b), "r"(c), "r"(d) : "memory");
}
__device__ __forceinline__ void bulk_load(uint32_t dst, const void* src, uint32_t bytes, uint32_t bar) {
    asm volatile("cp.async.bulk.shared::cluster.global.mbarrier::complete_tx::bytes [%0], [%1], %2, [%3];"
                 ::"r"(dst), "l"(src), "r"(bytes), "r"(bar) : "memory");
}
__device__ __forceinline__ uint32_t clock_now() {
    uint32_t t;
    asm volatile("mov.u32 %0, %%clock;" : "=r"(t) :: "memory");
    return t;
}
template <int BIT>
__device__ __forceinline__ void sched_fence(uint32_t zero) {
    asm volatile("{\n.reg .pred p;\n.reg .b32 t;\nand.b32 t, %0, %1;\nsetp.eq.u32 p, t, 0;\n@p bra SF_DONE;\ntrap;\nSF_DONE:\n}\n"
                 ::"r"(zero), "n"(1u << BIT) : "memory");
}
__device__ __forceinline__ float tanh_fast(float x) {
    float y;
    asm volatile("tanh.approx.f32 %0, %1;" : "=f"(y) : "f"(x));
    return y;
}
__device__ __forceinline__ void load_w_frags(uint32_t (&f)[4][4], uint32_t wa) {
#pragma unroll
    for (int kk = 0; kk < 4; kk++) ldsm_x4_trans(f[kk], wa + kk * 1024);
}
__device__ __forceinline__ void scale_w_frags(uint32_t (&f)[4][4]) {
#pragma unroll
    for (int kk = 0; kk < 4; kk++) {
        asm volatile("mul.rn.bf16x2 %0, %0, %1;" : "+r"(f[kk][1]) : "r"(0x3F003F00u));
        asm volatile("mul.rn.bf16x2 %0, %0, %1;" : "+r"(f[kk][3]) : "r"(0x3F003F00u));
    }
}
__device__ __forceinline__ uint32_t pack_bf16(float lo, float hi) {
    uint32_t r;
    asm("cvt.rn.bf16x2.f32 %0, %1, %2;" : "=r"(r) : "f"(hi), "f"(lo));
    return r;
}
__device__ __forceinline__ uint64_t make_desc(uint32_t addr, uint32_t lbo_bytes, uint32_t sbo_bytes) {
    return (uint64_t)((addr & 0x3FFFF) >> 4) | ((uint64_t)(lbo_bytes >> 4) << 16) | ((uint64_t)(sbo_bytes >> 4) << 32) |
           ((uint64_t)1 << 62);
}

#define R8(d, o) "+f"(d[o + 0]), "+f"(d[o + 1]), "+f"(d[o + 2]), "+f"(d[o + 3]), "+f"(d[o + 4]), "+f"(d[o + 5]), "+f"(d[o + 6]), "+f"(d[o + 7])

__device__ __forceinline__ void wgmma_m64n128k16_rs(float (&d)[64], const uint32_t (&a)[4], uint64_t descB) {
    asm volatile(
        "wgmma.mma_async.sync.aligned.m64n128k16.f32.bf16.bf16 "
        "{%0, %1, %2, %3, %4, %5, %6, %7, %8, %9, %10, %11, %12, %13, %14, %15, "
        "%16, %17, %18, %19, %20, %21, %22, %23, %24, %25, %26, %27, %28, %29, %30, %31, "
        "%32, %33, %34, %35, %36, %37, %38, %39, %40, %41, %42, %43, %44, %45, %46, %47, "
        "%48, %49, %50, %51, %52, %53, %54, %55, %56, %57, %58, %59, %60, %61, %62, %63}, "
        "{%64, %65, %66, %67}, %68, 1, -1, 1, 1;\n"
        : R8(d, 0), R8(d, 8), R8(d, 16), R8(d, 24), R8(d, 32), R8(d, 40), R8(d, 48), R8(d, 56)
        : "r"(a[0]), "r"(a[1]), "r"(a[2]), "r"(a[3]), "l"(descB));
}

__device__ __forceinline__ void wgmma_m64n64k16_rs(float (&d)[32], const uint32_t (&a)[4], uint64_t descB, int scale_d) {
    asm volatile(
        "{\n"
        ".reg .pred p;\n"
        "setp.ne.b32 p, %37, 0;\n"
        "wgmma.mma_async.sync.aligned.m64n64k16.f32.bf16.bf16 "
        "{%0, %1, %2, %3, %4, %5, %6, %7, %8, %9, %10, %11, %12, %13, %14, %15, "
        "%16, %17, %18, %19, %20, %21, %22, %23, %24, %25, %26, %27, %28, %29, %30, %31}, "
        "{%32, %33, %34, %35}, %36, p, -1, 1, 1;\n"
        "}\n"
        : R8(d, 0), R8(d, 8), R8(d, 16), R8(d, 24)
        : "r"(a[0]), "r"(a[1]), "r"(a[2]), "r"(a[3]), "l"(descB), "r"(scale_d));
}

template <int OFF>
__device__ __forceinline__ void wgmma_m64n128k16_rs_half(float (&d)[128], const uint32_t (&a)[4], uint64_t descB) {
    asm volatile(
        "wgmma.mma_async.sync.aligned.m64n128k16.f32.bf16.bf16 "
        "{%0, %1, %2, %3, %4, %5, %6, %7, %8, %9, %10, %11, %12, %13, %14, %15, "
        "%16, %17, %18, %19, %20, %21, %22, %23, %24, %25, %26, %27, %28, %29, %30, %31, "
        "%32, %33, %34, %35, %36, %37, %38, %39, %40, %41, %42, %43, %44, %45, %46, %47, "
        "%48, %49, %50, %51, %52, %53, %54, %55, %56, %57, %58, %59, %60, %61, %62, %63}, "
        "{%64, %65, %66, %67}, %68, 1, 1, 1, 0;\n"
        : R8(d, OFF + 0), R8(d, OFF + 8), R8(d, OFF + 16), R8(d, OFF + 24), R8(d, OFF + 32), R8(d, OFF + 40), R8(d, OFF + 48), R8(d, OFF + 56)
        : "r"(a[0]), "r"(a[1]), "r"(a[2]), "r"(a[3]), "l"(descB));
}
template <int OFF> __device__ __forceinline__ void fence_half(float (&d)[128]) {
#pragma unroll
    for (int i = 0; i < 64; i++) asm volatile("" : "+f"(d[OFF + i]) :: "memory");
}

template <int Q0, int N> struct GateGroup { static constexpr int J = 2 * (Q0 ^ (N >> 1)) + (N & 1); };

template <int Q0, int N>
__device__ __forceinline__ void gate_mufu(float (&acc)[128]) {
    constexpr int J = GateGroup<Q0, N>::J;
#pragma unroll
    for (int i = 0; i < 16; i++) acc[16 * J + i] = tanh_fast(acc[16 * J + i]);
}
template <int Q0, int N>
__device__ __forceinline__ void gate_finish(float (&acc)[128], uint8_t* zdst) {
    constexpr int J = GateGroup<Q0, N>::J;
    uint32_t zp[4];
#pragma unroll
    for (int i = 0; i < 4; i++) {
        const int r = 16 * J + 4 * i;
        zp[i] = __vmaxu2(pack_bf16(acc[r] * fmaf(acc[r + 2], -0.5f, -0.5f), acc[r + 1] * fmaf(acc[r + 3], -0.5f, -0.5f)), 0x00010001u);
    }
    st_relaxed_v4(zdst + (J >> 1) * 65536 + (J & 1) * 8192, zp[0], zp[1], zp[2], zp[3]);
    if (N & 1) asm volatile("bar.arrive %0, 160;" ::"n"(2 + (N >> 1)) : "memory");
}

template <int Q0>
__device__ __forceinline__ void tail_gemm1(float (&acc)[128], uint32_t (&afr)[2][4][4], uint32_t sb, int ws, int wph, uint32_t a_lane_off,
                                           uint8_t* zdst, int lane, uint32_t zero) {
    constexpr int OA = (Q0 >> 1) * 64;
    constexpr int OB = 64 - OA;
    const uint32_t bars = sb + SM_BAR;
    uint32_t fa[4][4], fb[4][4], fc[4][4];
    const int ws0 = ws;
    auto wtile = [&](int tap) { return sb + SM_W + ((ws0 + tap) & (WST - 1)) * WBYTES + a_lane_off; };
    auto wwait = [&](int tap) {
        const int st = ws0 + tap;
        mbar_wait(bars + 8 * (BAR_WFULL + (st & (WST - 1))), wph ^ ((st >> 2) & 1));
    };
    auto load = [&](uint32_t (&f)[4][4], int tap) { load_w_frags(f, wtile(tap)); };
    auto issueA = [&](uint32_t (&f)[4][4], int tap) {
        const uint64_t db = make_desc(sb + SM_X + XBYTES + (8 - 2 * tap) * 128 + OA * 256, 16, 1024);
        wgmma_fence();
#pragma unroll
        for (int kk = 0; kk < 4; kk++) wgmma_m64n128k16_rs_half<OA>(acc, f[kk], db + kk * 2);
        wgmma_commit();
    };
    auto issueB = [&](uint32_t (&f)[4][4], int tap) {
        const uint64_t db = make_desc(sb + SM_X + XBYTES + (8 - 2 * tap) * 128 + OB * 256, 16, 1024);
        wgmma_fence();
#pragma unroll
        for (int kk = 0; kk < 4; kk++) wgmma_m64n128k16_rs_half<OB>(acc, f[kk], db + kk * 2);
        wgmma_commit();
    };
    mbar_wait(bars + 8 * (BAR_XFULL + 1), 1);
    wwait(0); load(fa, 0);
    __syncwarp();
    if (lane == 0) mbar_arrive(bars + 8 * (BAR_WEMPTY + ws0));
    wwait(1); load(fb, 1);
    wwait(2); load(fc, 2);
    scale_w_frags(fa); issueA(fa, 0); wgmma_wait<1>();
    wwait(3); load(afr[0], 3);
    scale_w_frags(fb); issueA(fb, 1);
    scale_w_frags(fc); issueA(fc, 2);
    wwait(4); load(afr[1], 4);
    scale_w_frags(afr[0]); issueA(afr[0], 3);
    scale_w_frags(afr[1]); issueA(afr[1], 4);
    if (threadIdx.x == 0) PROF(24);
    issueB(fa, 0);
    issueB(fb, 1);
    wgmma_wait<2>();
    fence_half<OA>(acc);
    sched_fence<0>(zero);
    gate_mufu<Q0, 0>(acc); gate_mufu<Q0, 1>(acc);
    gate_finish<Q0, 0>(acc, zdst); gate_finish<Q0, 1>(acc, zdst);
    sched_fence<1>(zero);
    issueB(fc, 2);
    issueB(afr[0], 3);
    sched_fence<2>(zero);
    gate_mufu<Q0, 2>(acc); gate_mufu<Q0, 3>(acc);
    sched_fence<3>(zero);
    issueB(afr[1], 4);
    sched_fence<4>(zero);
    gate_finish<Q0, 2>(acc, zdst); gate_finish<Q0, 3>(acc, zdst);
    wgmma_wait<0>();
    fence_half<OB>(acc);
    if (threadIdx.x == 0) PROF(3);
    gate_mufu<Q0, 4>(acc);
    gate_mufu<Q0, 5>(acc);
    gate_finish<Q0, 4>(acc, zdst);
    gate_finish<Q0, 5>(acc, zdst);
    sched_fence<5>(zero);
    gate_mufu<Q0, 6>(acc);
    gate_mufu<Q0, 7>(acc);
    gate_finish<Q0, 6>(acc, zdst);
    gate_finish<Q0, 7>(acc, zdst);
}

__device__ __forceinline__ void fetch_slot(int i, uint32_t sb, const uint8_t* zsrc, int q, int lane) {
    const uint32_t bars = sb + SM_BAR;
    asm volatile("bar.sync %0, 160;" ::"r"(2 + i) : "memory");
    if (lane == 0) {
        uint32_t t;
        asm volatile("mov.u32 %0, %%clock;" : "=r"(t) : "r"(lane) : "memory");
        const uint32_t delay = (i == 0) ? ZDELAY0 : (i == 1) ? ZDELAY1 : (i == 2) ? ZDELAY2 : ZDELAY3;
        while (clock_now() - t < delay) {}
        mbar_expect_tx(bars + 8 * (BAR_Z + i), 16384);
        bulk_load(sb + sm_zin(i), zsrc + (q ^ i) * 16384, 16384, bars + 8 * (BAR_Z + i));
        PROF(26 + i);
    }
    __syncwarp();
}

template <int I>
__device__ __forceinline__ void z_load(uint32_t (&z)[8][4], uint32_t sb, int warp, int lane) {
    mbar_wait(sb + SM_BAR + 8 * (BAR_Z + I), 0);
#pragma unroll
    for (int j = 0; j < 8; j++) ldsm_x4_trans(z[j], sb + sm_zin(I) + warp * 4096 + j * 512 + lane * 16);
}
__device__ __forceinline__ bool z_check(const uint32_t (&z)[8][4]) {
    uint32_t m0 = 0xFFFFFFFFu, m1 = 0xFFFFFFFFu;
#pragma unroll
    for (int j = 0; j < 8; j++) {
        m0 = __vimin3_u16x2(m0, z[j][0], z[j][1]);
        m1 = __vimin3_u16x2(m1, z[j][2], z[j][3]);
    }
    m0 = __vminu2(m0, m1);
    return __all_sync(0xffffffffu, ((m0 & 0xFFFFu) != 0u) && ((m0 >> 16) != 0u));
}
__device__ __forceinline__ void z_issue(float (&acc2)[64], uint32_t (&z)[8][4], uint32_t sb, int beta) {
#pragma unroll
    for (int j = 0; j < 8; j++) asm volatile("" : "+r"(z[j][0]), "+r"(z[j][1]), "+r"(z[j][2]), "+r"(z[j][3]) :: "memory");
    const uint64_t db = make_desc(sb + SM_WO + beta * 16384, 65536, 1024);
    wgmma_fence();
#pragma unroll
    for (int j = 0; j < 8; j++) wgmma_m64n128k16_rs(acc2, z[j], db + j * 128);
    wgmma_commit();
}
__device__ __forceinline__ bool wg_any(bool p) {
    uint32_t r;
    asm volatile("{\n.reg .pred a, b;\nsetp.ne.u32 a, %1, 0;\nbarrier.cta.red.or.aligned.pred b, 1, 128, a;\nselp.u32 %0, 1, 0, b;\n}\n"
                 : "=r"(r) : "r"((uint32_t)p) : "memory");
    return r != 0;
}
template <int I>
__device__ __forceinline__ void z_repair(float (&acc2)[64], uint32_t sb, const uint8_t* src, int beta, int warp, int lane, uint32_t mine,
                                         uint32_t& rph) {
    if (!wg_any(mine != 0u)) return;
    uint32_t z[8][4];
    if (mine) {
        const uint32_t zo = sb + sm_zin(I) + warp * 4096;
        const uint32_t zs = sb + SM_ZFIX + warp * 4096;
        const uint32_t bar = sb + SM_BAR + 8 * (BAR_RETRY + warp);
        int spins = 0;
        do {
            __syncwarp();
            if (lane == 0) {
                mbar_expect_tx(bar, 4096);
                bulk_load(zs, src, 4096, bar);
            }
            mbar_wait(bar, rph);
            rph ^= 1;
#pragma unroll
            for (int j = 0; j < 8; j++) ldsm_x4_trans(z[j], zs + j * 512 + lane * 16);
        } while (!z_check(z) && ++spins < (1 << 16));
#pragma unroll
        for (int j = 0; j < 8; j++) {
            uint32_t o[4];
            ldsm_x4_trans(o, zo + j * 512 + lane * 16);
#pragma unroll
            for (int k = 0; k < 4; k++) z[j][k] &= __vcmpeq2(o[k], 0u);
        }
    } else {
#pragma unroll
        for (int j = 0; j < 8; j++)
#pragma unroll
            for (int k = 0; k < 4; k++) z[j][k] = 0u;
    }
    z_issue(acc2, z, sb, beta);
    wgmma_wait<0>();
}

template <int H>
__device__ __forceinline__ void store_half(const float (&a)[64], const float (&b)[32], uint32_t stg, __nv_bfloat16* obase, int tbase, int lane) {
    const int row = lane & 15, csel = lane >> 4;
#pragma unroll
    for (int j2 = 0; j2 < 4; j2++) {
        const int j = 2 * j2, o = 32 * H + 4 * j;
        const uint32_t r0 = pack_bf16(a[o + 0] + b[4 * j + 0], a[o + 1] + b[4 * j + 1]);
        const uint32_t r1 = pack_bf16(a[o + 2] + b[4 * j + 2], a[o + 3] + b[4 * j + 3]);
        const uint32_t r2 = pack_bf16(a[o + 4] + b[4 * j + 4], a[o + 5] + b[4 * j + 5]);
        const uint32_t r3 = pack_bf16(a[o + 6] + b[4 * j + 6], a[o + 7] + b[4 * j + 7]);
        stsm_x4(stg + H * 2048 + row * 128 + (((j + csel) ^ (row & 7)) << 4), r0, r1, r2, r3);
    }
    __syncwarp();
#pragma unroll
    for (int i = 0; i < 4; i++) {
        const int r = 4 * i + (lane >> 3);
        const int ch = lane & 7;
        const int tok = tbase + ((r & 7) >> 1) * 8 + (r >> 3) * 2 + (r & 1);
        uint4 v;
        asm volatile("ld.shared.v4.b32 {%0, %1, %2, %3}, [%4];" : "=r"(v.x), "=r"(v.y), "=r"(v.z), "=r"(v.w)
                     : "r"(stg + H * 2048 + r * 128 + ((ch ^ (r & 7)) << 4)) : "memory");
        if (tok < T_LEN) *reinterpret_cast<uint4*>(obase + (size_t)tok * D_CH + H * 64 + ch * 8) = v;
    }
}

__global__ void __launch_bounds__(NTHREADS, 1)
wavenet_fused_kernel(const __grid_constant__ CUtensorMap mapX, const __grid_constant__ CUtensorMap mapW,
                     const __grid_constant__ CUtensorMap mapWo, __nv_bfloat16* __restrict__ out, const uint32_t zero) {
    extern __shared__ __align__(1024) uint8_t smem_raw[];
    const uint32_t sb = smem_u32(smem_raw);
    const uint32_t bars = sb + SM_BAR;
    const int warp = threadIdx.x >> 5;
    const int lane = threadIdx.x & 31;
    const int cg = blockIdx.x & 15;
    const int tt = blockIdx.x >> 4;
    const int batch = tt >> 2;
    const int t0 = (tt & 3) * NTOK;
    const int c4 = cg & 3, q = cg >> 2;

    if (threadIdx.x == 160) {
        prefetch_tmap(&mapW);
        prefetch_tmap(&mapX);
    }
    if (threadIdx.x == 128) {
        PROFG(0);
        const uint32_t xf = bars + 8 * BAR_XFULL;
        mbar_init(xf, 1);
        mbar_init(bars + 8 * BAR_WFULL, 1);
        asm volatile("fence.mbarrier_init.release.cluster;" ::: "memory");
        fence_proxy_async_smem();
        mbar_expect_tx(bars + 8 * BAR_WFULL, WBYTES);
        tma_load_3d(sb + SM_W, &mapW, bars + 8 * BAR_WFULL, cg * 32, 0, 0);
        mbar_expect_tx(xf, XBYTES);
#pragma unroll
        for (int j = 0; j < 3; j++) tma_load_3d(sb + SM_X + j * XBOX * 128, &mapX, xf, 0, t0 - 8 + j * XBOX, batch);
        for (int i = 1; i < WST; i++) mbar_init(bars + 8 * (BAR_WFULL + i), 1);
        asm volatile("fence.mbarrier_init.release.cluster;" ::: "memory");
        fence_proxy_async_smem();
#pragma unroll
        for (int i = 1; i < WST; i++) {
            mbar_expect_tx(bars + 8 * (BAR_WFULL + i), WBYTES);
            tma_load_3d(sb + SM_W + i * WBYTES, &mapW, bars + 8 * (BAR_WFULL + i), cg * 32, i * 512, 0);
        }
    } else if (threadIdx.x == 0) {
        for (int i = 0; i < WST; i++) mbar_init(bars + 8 * (BAR_WEMPTY + i), 4);
        mbar_init(bars + 8 * (BAR_XFULL + 1), 1);
        for (int i = 0; i < XST; i++) mbar_init(bars + 8 * (BAR_XEMPTY + i), 4);
        mbar_init(bars + 8 * BAR_WO, 1);
        mbar_init(bars + 8 * BAR_PAR, 1);
        for (int i = 0; i < 4; i++) {
            mbar_init(bars + 8 * (BAR_Z + i), 1);
            mbar_init(bars + 8 * (BAR_RETRY + i), 1);
        }
        asm volatile("fence.mbarrier_init.release.cluster;" ::: "memory");
    }
    __syncthreads();

    if (warp >= 4) {
        if (warp == 4) {
            if (lane == 0) {
                int ws = 0, wph = 0;
                for (int kc = 0; kc < 8; kc++) {
                    const int xs = kc & 1;
                    if (kc > 0) {
                        mbar_wait(bars + 8 * (BAR_XEMPTY + xs), ((kc >> 1) & 1) ^ 1);
                        const uint32_t xf = bars + 8 * (BAR_XFULL + xs);
                        mbar_expect_tx(xf, XBYTES);
                        const uint32_t xd = sb + SM_X + xs * XBYTES;
#pragma unroll
                        for (int j = 0; j < 3; j++) tma_load_3d(xd + j * XBOX * 128, &mapX, xf, kc * 64, t0 - 8 + j * XBOX, batch);
                    } else {
                        prefetch_tmap(&mapWo);
                    }
                    for (int tap = (kc == 0 ? WST : 0); tap < 5; tap++) {
                        mbar_wait(bars + 8 * (BAR_WEMPTY + ws), wph);
                        const uint32_t wf = bars + 8 * (BAR_WFULL + ws);
                        mbar_expect_tx(wf, WBYTES);
                        tma_load_3d(sb + SM_W + ws * WBYTES, &mapW, wf, cg * 32, tap * 512 + kc * 64, 0);
                        if (++ws == WST) { ws = 0; wph ^= 1; }
                        const int it = kc * 5 + tap - 10;
                        if (it >= 0 && it < 16) {
                            const uint32_t wob = bars + 8 * BAR_WO;
                            if (it == 0) mbar_expect_tx(wob, WO_BYTES);
                            tma_load_2d(sb + SM_WO + (it & 1) * 65536 + (it >> 1) * 8192, &mapWo, wob, c4 * 128 + (it & 1) * 64, (it >> 1) * 64);
                        }
                    }
                }
            }
            __syncwarp();
        } else if (warp == 5) {
            unsigned int par = 0;
            if (lane == 0) par = (atomicAdd(&g_ticket, 1u) >> 7) & 1u;
            par = __shfl_sync(0xffffffffu, par, 0);
            __nanosleep(1500);
            uint4* mine = &g_zx[par][tt * 4 * 4096 + q * 1024 + 2 * c4 * 32];
#pragma unroll 1
            for (int i = 0; i < 32; i++) {
                mine[(i >> 3) * 4096 + ((i >> 1) & 3) * 256 + (i & 1) * 32 + lane] = make_uint4(0u, 0u, 0u, 0u);
                __nanosleep(100);
            }
            __syncwarp();
            if (lane == 0) {
                asm volatile("st.shared.u32 [%0], %1;" ::"r"(sb + SM_PAR), "r"(par) : "memory");
                mbar_arrive(bars + 8 * BAR_PAR);
            }
            uint4* clr = &g_zx[par ^ 1][blockIdx.x * 1024];
#pragma unroll 1
            for (int i = 0; i < 32; i++) {
                clr[i * 32 + lane] = make_uint4(0u, 0u, 0u, 0u);
                __nanosleep(100);
            }
        }
        mbar_wait(bars + 8 * BAR_PAR, 0);
        uint32_t par;
        asm volatile("ld.shared.u32 %0, [%1];" : "=r"(par) : "r"(sb + SM_PAR) : "memory");
        const uint8_t* zsrc = reinterpret_cast<const uint8_t*>(&g_zx[par][(tt * 4 + q) * 4096]);
        fetch_slot(7 - warp, sb, zsrc, q, lane);
    } else {
        float acc[128];
#pragma unroll
        for (int i = 0; i < 128; i++) acc[i] = 0.f;
        uint32_t afr[2][4][4];
        const int lk = ((lane >> 4) << 3) + (lane & 7);
        const uint32_t a_lane_off = ((lane >> 3) & 1) * 4096 + lk * 64 + ((warp ^ ((lk >> 1) & 3)) << 4);
        int ws = 0, wph = 0;
        uint32_t par = 0;
        if (threadIdx.x == 0) PROF(1);
#pragma unroll 1
        for (int kc2 = 0; kc2 < 4; kc2++) {
#pragma unroll
            for (int u = 0; u < 10; u++) {
                const int xs = u / 5;
                const int tap = u % 5;
                if (u == 5 && kc2 == 3) break;
                if (tap == 0) mbar_wait(bars + 8 * (BAR_XFULL + xs), kc2 & 1);
                mbar_wait(bars + 8 * (BAR_WFULL + ws), wph);
                if (kc2 == 0 && u == 0 && threadIdx.x == 0) PROF(2);
                const uint32_t wa = sb + SM_W + ws * WBYTES + a_lane_off;
                load_w_frags(afr[u & 1], wa);
                __syncwarp();
                if (lane == 0) mbar_arrive(bars + 8 * (BAR_WEMPTY + ws));
                scale_w_frags(afr[u & 1]);
                if (++ws == WST) { ws = 0; wph ^= 1; }
                const uint64_t db = make_desc(sb + SM_X + xs * XBYTES + (8 - 2 * tap) * 128, 16, 1024);
                wgmma_fence();
#pragma unroll
                for (int kk = 0; kk < 4; kk++) {
                    wgmma_m64n128k16_rs_half<0>(acc, afr[u & 1][kk], db + kk * 2);
                    wgmma_m64n128k16_rs_half<64>(acc, afr[u & 1][kk], db + kk * 2 + 1024);
                }
                wgmma_commit();
                if (u == 2 && kc2 == 3) {
                    mbar_wait(bars + 8 * BAR_PAR, 0);
                    asm volatile("ld.shared.u32 %0, [%1];" : "=r"(par) : "r"(sb + SM_PAR) : "memory");
                    mbar_wait(bars + 8 * BAR_WO, 0);
                }
                wgmma_wait<1>();
                if (tap == 0 && (u > 0 || kc2 > 0)) {
                    if (lane == 0) mbar_arrive(bars + 8 * (BAR_XEMPTY + (xs ^ 1)));
                }
            }
        }
        uint8_t* zx = reinterpret_cast<uint8_t*>(&g_zx[par][tt * 4 * 4096]);
        uint8_t* zdst = zx + q * 16384 + (2 * c4 + (warp >> 1)) * 512 + (warp & 1) * 256 +
                        ((lane >> 1) & 1) * 4096 + (lane & 1) * 128 + (lane >> 2) * 16;
        switch (q) {
            case 0: tail_gemm1<0>(acc, afr, sb, ws, wph, a_lane_off, zdst, lane, zero); break;
            case 1: tail_gemm1<1>(acc, afr, sb, ws, wph, a_lane_off, zdst, lane, zero); break;
            case 2: tail_gemm1<2>(acc, afr, sb, ws, wph, a_lane_off, zdst, lane, zero); break;
            default: tail_gemm1<3>(acc, afr, sb, ws, wph, a_lane_off, zdst, lane, zero); break;
        }
        if (threadIdx.x == 0) PROF(4);

        float acc2[64], acc3a[32], acc3b[32];
#pragma unroll
        for (int i = 0; i < 64; i++) acc2[i] = 0.f;
        uint32_t bad;
        {
            uint32_t za[3][8][4];
            z_load<0>(za[0], sb, warp, lane);
            if (threadIdx.x == 0) PROF(12);
            z_issue(acc2, za[0], sb, q ^ 0);
            z_load<1>(za[1], sb, warp, lane);
            bad = z_check(za[0]) ? 0u : 1u;
            if (threadIdx.x == 0) PROF(13);
            z_issue(acc2, za[1], sb, q ^ 1);
            z_load<2>(za[2], sb, warp, lane);
            bad |= z_check(za[1]) ? 0u : 2u;
            if (threadIdx.x == 0) PROF(14);
            z_issue(acc2, za[2], sb, q ^ 2);
            wgmma_wait<2>();
            z_load<3>(za[0], sb, warp, lane);
            bad |= z_check(za[2]) ? 0u : 4u;
            if (threadIdx.x == 0) PROF(15);
#pragma unroll
            for (int j = 0; j < 8; j++) asm volatile("" : "+r"(za[0][j][0]), "+r"(za[0][j][1]), "+r"(za[0][j][2]), "+r"(za[0][j][3]) :: "memory");
            const uint64_t db = make_desc(sb + SM_WO + (q ^ 3) * 16384, 65536, 1024);
            wgmma_fence();
#pragma unroll
            for (int j = 0; j < 8; j++) wgmma_m64n64k16_rs(acc3a, za[0][j], db + j * 128, j);
            wgmma_commit();
#pragma unroll
            for (int j = 0; j < 8; j++) wgmma_m64n64k16_rs(acc3b, za[0][j], db + j * 128 + 4096, j);
            wgmma_commit();
            sched_fence<7>(zero);
            bad |= z_check(za[0]) ? 0u : 8u;
        }
        const uint32_t stg = sb + SM_OSTG + warp * 4096;
        const int tbase = t0 + q * 64 + (warp >> 1) * 32 + (warp & 1) * 4;
        __nv_bfloat16* obase = out + (size_t)batch * T_LEN * D_CH + c4 * 128;
        wgmma_wait<1>();
        fence_regs(acc2);
        fence_regs(acc3a);
        if (threadIdx.x == 0) PROF(10);
        store_half<0>(acc2, acc3a, stg, obase, tbase, lane);
        wgmma_wait<0>();
        fence_regs(acc3b);
        store_half<1>(acc2, acc3b, stg, obase, tbase, lane);
        if (__builtin_expect(wg_any(bad != 0u), 0)) {
            const uint8_t* zsrc = zx + q * 65536 + warp * 4096;
            uint32_t rph = 0;
            z_repair<0>(acc2, sb, zsrc + (q ^ 0) * 16384, q ^ 0, warp, lane, bad & 1u, rph);
            z_repair<1>(acc2, sb, zsrc + (q ^ 1) * 16384, q ^ 1, warp, lane, bad & 2u, rph);
            z_repair<2>(acc2, sb, zsrc + (q ^ 2) * 16384, q ^ 2, warp, lane, bad & 4u, rph);
            z_repair<3>(acc2, sb, zsrc + (q ^ 3) * 16384, q ^ 3, warp, lane, bad & 8u, rph);
            fence_regs(acc2);
            __syncwarp();
            store_half<0>(acc2, acc3a, stg, obase, tbase, lane);
            store_half<1>(acc2, acc3b, stg, obase, tbase, lane);
        }
        if (threadIdx.x == 0) PROFG(11);
    }
}

typedef CUresult (*EncodeFn)(CUtensorMap*, CUtensorMapDataType, cuuint32_t, void*, const cuuint64_t*, const cuuint64_t*,
                             const cuuint32_t*, const cuuint32_t*, CUtensorMapInterleave, CUtensorMapSwizzle,
                             CUtensorMapL2promotion, CUtensorMapFloatOOBfill);

void encode(EncodeFn fn, CUtensorMap* m, const void* ptr, int rank, const cuuint64_t* dims, const cuuint64_t* strides,
            const cuuint32_t* box, CUtensorMapSwizzle sw) {
    cuuint32_t es[3] = {1, 1, 1};
    fn(m, CU_TENSOR_MAP_DATA_TYPE_BFLOAT16, rank, const_cast<void*>(ptr), dims, strides, box, es,
       CU_TENSOR_MAP_INTERLEAVE_NONE, sw, CU_TENSOR_MAP_L2_PROMOTION_L2_128B, CU_TENSOR_MAP_FLOAT_OOB_FILL_NONE);
}

}

extern "C" void kernel_launch(void* const* d_in, const int* in_sizes, int n_in, void* d_out, int out_size) {
    (void)in_sizes; (void)n_in; (void)out_size;
    static EncodeFn enc = nullptr;
    if (!enc) {
        void* fn = nullptr;
        cudaDriverEntryPointQueryResult qr;
        cudaGetDriverEntryPoint("cuTensorMapEncodeTiled", &fn, cudaEnableDefault, &qr);
        enc = (EncodeFn)fn;
        cudaFuncSetAttribute(wavenet_fused_kernel, cudaFuncAttributeMaxDynamicSharedMemorySize, SM_TOTAL);
    }
    CUtensorMap mX, mW, mWo;
    {
        cuuint64_t dims[3] = {512, (cuuint64_t)T_LEN, 2}, str[2] = {1024, (cuuint64_t)T_LEN * 1024};
        cuuint32_t box[3] = {64, XBOX, 1};
        encode(enc, &mX, d_in[0], 3, dims, str, box, CU_TENSOR_MAP_SWIZZLE_128B);
    }
    {
        cuuint64_t dims[3] = {512, 2560, 2}, str[2] = {2048, 1024};
        cuuint32_t box[3] = {32, 64, 2};
        encode(enc, &mW, d_in[1], 3, dims, str, box, CU_TENSOR_MAP_SWIZZLE_64B);
    }
    {
        cuuint64_t dims[2] = {512, 512}, str[1] = {1024};
        cuuint32_t box[2] = {64, 64};
        encode(enc, &mWo, d_in[2], 2, dims, str, box, CU_TENSOR_MAP_SWIZZLE_128B);
    }
    wavenet_fused_kernel<<<128, NTHREADS, SM_TOTAL>>>(mX, mW, mWo, (__nv_bfloat16*)d_out, 0u);
}
```

```cpp
#include <cuda_runtime.h>
#include <cuda_bf16.h>
#include <cuda.h>
#include <stdint.h>

namespace {

constexpr int T_LEN   = 1000;
constexpr int D_CH    = 512;
constexpr int NTOK    = 256;
constexpr int XROWS   = NTOK + 8;
constexpr int XBYTES  = XROWS * 128;
constexpr int XBOX    = 88;
constexpr int XST     = 2;
constexpr int WST     = 4;
constexpr int WBYTES  = 8192;
constexpr int WO_BYTES = 131072;

constexpr int SM_WO   = 0;
constexpr int SM_X    = SM_WO + WO_BYTES;
constexpr int SM_W    = SM_X + XST * XBYTES;
constexpr int SM_BAR  = SM_W + WST * WBYTES;
constexpr int SM_TOTAL = SM_BAR + 256;
__host__ __device__ constexpr int sm_zin(int i) { return SM_X + (i >> 1) * XBYTES + (i & 1) * 16384; }
constexpr int SM_OSTG  = SM_W;
constexpr int SM_ZFIX  = SM_W + 16384;

constexpr int BAR_WFULL  = 0;
constexpr int BAR_WEMPTY = BAR_WFULL + WST;
constexpr int BAR_XFULL  = BAR_WEMPTY + WST;
constexpr int BAR_XEMPTY = BAR_XFULL + XST;
constexpr int BAR_WO     = BAR_XEMPTY + XST;
constexpr int BAR_PAR    = BAR_WO + 1;
constexpr int BAR_Z      = BAR_PAR + 1;
constexpr int BAR_RETRY  = BAR_Z + 4;

constexpr int SM_PAR   = SM_BAR + 240;
constexpr int NTHREADS = 256;
#define ZDELAY0 650
#define ZDELAY1 600
#define ZDELAY2 650
#define ZDELAY3 600

__device__ uint4 g_zx[2][8 * 4 * 4096];
__device__ unsigned int g_ticket;

#define PROF(i)
#define PROFG(i)

__device__ __forceinline__ uint32_t smem_u32(const void* p) { return (uint32_t)__cvta_generic_to_shared(p); }

__device__ __forceinline__ void mbar_init(uint32_t bar, uint32_t cnt) {
    asm volatile("mbarrier.init.shared::cta.b64 [%0], %1;" ::"r"(bar), "r"(cnt));
}
__device__ __forceinline__ void mbar_expect_tx(uint32_t bar, uint32_t bytes) {
    asm volatile("mbarrier.arrive.expect_tx.shared::cta.b64 _, [%0], %1;" ::"r"(bar), "r"(bytes) : "memory");
}
__device__ __forceinline__ void mbar_arrive(uint32_t bar) {
    asm volatile("mbarrier.arrive.shared::cta.b64 _, [%0];" ::"r"(bar) : "memory");
}
__device__ __forceinline__ void mbar_wait(uint32_t bar, uint32_t parity) {
    asm volatile(
        "{\n"
        ".reg .pred p;\n"
        "WAIT_LOOP:\n"
        "mbarrier.try_wait.parity.shared::cta.b64 p, [%0], %1;\n"
        "@p bra WAIT_DONE;\n"
        "bra WAIT_LOOP;\n"
        "WAIT_DONE:\n"
        "}\n" ::"r"(bar), "r"(parity) : "memory");
}
__device__ __forceinline__ void tma_load_3d(uint32_t dst, const CUtensorMap* m, uint32_t bar, int c0, int c1, int c2) {
    asm volatile("cp.async.bulk.tensor.3d.shared::cluster.global.mbarrier::complete_tx::bytes [%0], [%1, {%3, %4, %5}], [%2];"
                 ::"r"(dst), "l"(m), "r"(bar), "r"(c0), "r"(c1), "r"(c2) : "memory");
}
__device__ __forceinline__ void tma_load_2d(uint32_t dst, const CUtensorMap* m, uint32_t bar, int c0, int c1) {
    asm volatile("cp.async.bulk.tensor.2d.shared::cluster.global.mbarrier::complete_tx::bytes [%0], [%1, {%3, %4}], [%2];"
                 ::"r"(dst), "l"(m), "r"(bar), "r"(c0), "r"(c1) : "memory");
}
__device__ __forceinline__ void fence_proxy_async_smem() { asm volatile("fence.proxy.async.shared::cta;" ::: "memory"); }
__device__ __forceinline__ void prefetch_tmap(const CUtensorMap* m) {
    asm volatile("prefetch.tensormap [%0];" ::"l"(m) : "memory");
}
__device__ __forceinline__ void wgmma_fence() { asm volatile("wgmma.fence.sync.aligned;" ::: "memory"); }
__device__ __forceinline__ void wgmma_commit() { asm volatile("wgmma.commit_group.sync.aligned;" ::: "memory"); }
template <int N> __device__ __forceinline__ void wgmma_wait() {
    asm volatile("wgmma.wait_group.sync.aligned %0;" ::"n"(N) : "memory");
}
template <int N> __device__ __forceinline__ void fence_regs(float (&d)[N]) {
#pragma unroll
    for (int i = 0; i < N; i++) asm volatile("" : "+f"(d[i]) :: "memory");
}
__device__ __forceinline__ void ldsm_x4_trans(uint32_t (&r)[4], uint32_t addr) {
    asm volatile("ldmatrix.sync.aligned.m8n8.x4.trans.shared.b16 {%0, %1, %2, %3}, [%4];"
                 : "=r"(r[0]), "=r"(r[1]), "=r"(r[2]), "=r"(r[3]) : "r"(addr) : "memory");
}
__device__ __forceinline__ void stsm_x4(uint32_t addr, uint32_t a, uint32_t b, uint32_t c, uint32_t d) {
    asm volatile("stmatrix.sync.aligned.m8n8.x4.shared.b16 [%0], {%1, %2, %3, %4};"
                 ::"r"(addr), "r"(a), "r"(b), "r"(c), "r"(d) : "memory");
}
__device__ __forceinline__ void st_relaxed_v4(void* p, uint32_t a, uint32_t b, uint32_t c, uint32_t d) {
    asm volatile("st.relaxed.gpu.global.v4.b32 [%0], {%1, %2, %3, %4};" ::"l"(p), "r"(a), "r"(b), "r"(c), "r"(d) : "memory");
}
__device__ __forceinline__ void bulk_load(uint32_t dst, const void* src, uint32_t bytes, uint32_t bar) {
    asm volatile("cp.async.bulk.shared::cluster.global.mbarrier::complete_tx::bytes [%0], [%1], %2, [%3];"
                 ::"r"(dst), "l"(src), "r"(bytes), "r"(bar) : "memory");
}
__device__ __forceinline__ uint32_t clock_now() {
    uint32_t t;
    asm volatile("mov.u32 %0, %%clock;" : "=r"(t) :: "memory");
    return t;
}
template <int BIT>
__device__ __forceinline__ void sched_fence(uint32_t zero) {
    asm volatile("{\n.reg .pred p;\n.reg .b32 t;\nand.b32 t, %0, %1;\nsetp.eq.u32 p, t, 0;\n@p bra SF_DONE;\ntrap;\nSF_DONE:\n}\n"
                 ::"r"(zero), "n"(1u << BIT) : "memory");
}
__device__ __forceinline__ float tanh_fast(float x) {
    float y;
    asm volatile("tanh.approx.f32 %0, %1;" : "=f"(y) : "f"(x));
    return y;
}
__device__ __forceinline__ void load_w_frags(uint32_t (&f)[4][4], uint32_t wa) {
#pragma unroll
    for (int kk = 0; kk < 4; kk++) ldsm_x4_trans(f[kk], wa + kk * 1024);
}
__device__ __forceinline__ void scale_w_frags(uint32_t (&f)[4][4]) {
#pragma unroll
    for (int kk = 0; kk < 4; kk++) {
        asm volatile("mul.rn.bf16x2 %0, %0, %1;" : "+r"(f[kk][1]) : "r"(0x3F003F00u));
        asm volatile("mul.rn.bf16x2 %0, %0, %1;" : "+r"(f[kk][3]) : "r"(0x3F003F00u));
    }
}
__device__ __forceinline__ uint32_t pack_bf16(float lo, float hi) {
    uint32_t r;
    asm("cvt.rn.bf16x2.f32 %0, %1, %2;" : "=r"(r) : "f"(hi), "f"(lo));
    return r;
}
__device__ __forceinline__ uint64_t make_desc(uint32_t addr, uint32_t lbo_bytes, uint32_t sbo_bytes) {
    return (uint64_t)((addr & 0x3FFFF) >> 4) | ((uint64_t)(lbo_bytes >> 4) << 16) | ((uint64_t)(sbo_bytes >> 4) << 32) |
           ((uint64_t)1 << 62);
}

#define R8(d, o) "+f"(d[o + 0]), "+f"(d[o + 1]), "+f"(d[o + 2]), "+f"(d[o + 3]), "+f"(d[o + 4]), "+f"(d[o + 5]), "+f"(d[o + 6]), "+f"(d[o + 7])

__device__ __forceinline__ void wgmma_m64n128k16_rs(float (&d)[64], const uint32_t (&a)[4], uint64_t descB) {
    asm volatile(
        "wgmma.mma_async.sync.aligned.m64n128k16.f32.bf16.bf16 "
        "{%0, %1, %2, %3, %4, %5, %6, %7, %8, %9, %10, %11, %12, %13, %14, %15, "
        "%16, %17, %18, %19, %20, %21, %22, %23, %24, %25, %26, %27, %28, %29, %30, %31, "
        "%32, %33, %34, %35, %36, %37, %38, %39, %40, %41, %42, %43, %44, %45, %46, %47, "
        "%48, %49, %50, %51, %52, %53, %54, %55, %56, %57, %58, %59, %60, %61, %62, %63}, "
        "{%64, %65, %66, %67}, %68, 1, -1, 1, 1;\n"
        : R8(d, 0), R8(d, 8), R8(d, 16), R8(d, 24), R8(d, 32), R8(d, 40), R8(d, 48), R8(d, 56)
        : "r"(a[0]), "r"(a[1]), "r"(a[2]), "r"(a[3]), "l"(descB));
}

__device__ __forceinline__ void wgmma_m64n64k16_rs(float (&d)[32], const uint32_t (&a)[4], uint64_t descB, int scale_d) {
    asm volatile(
        "{\n"
        ".reg .pred p;\n"
        "setp.ne.b32 p, %37, 0;\n"
        "wgmma.mma_async.sync.aligned.m64n64k16.f32.bf16.bf16 "
        "{%0, %1, %2, %3, %4, %5, %6, %7, %8, %9, %10, %11, %12, %13, %14, %15, "
        "%16, %17, %18, %19, %20, %21, %22, %23, %24, %25, %26, %27, %28, %29, %30, %31}, "
        "{%32, %33, %34, %35}, %36, p, -1, 1, 1;\n"
        "}\n"
        : R8(d, 0), R8(d, 8), R8(d, 16), R8(d, 24)
        : "r"(a[0]), "r"(a[1]), "r"(a[2]), "r"(a[3]), "l"(descB), "r"(scale_d));
}

template <int OFF>
__device__ __forceinline__ void wgmma_m64n128k16_rs_half(float (&d)[128], const uint32_t (&a)[4], uint64_t descB) {
    asm volatile(
        "wgmma.mma_async.sync.aligned.m64n128k16.f32.bf16.bf16 "
        "{%0, %1, %2, %3, %4, %5, %6, %7, %8, %9, %10, %11, %12, %13, %14, %15, "
        "%16, %17, %18, %19, %20, %21, %22, %23, %24, %25, %26, %27, %28, %29, %30, %31, "
        "%32, %33, %34, %35, %36, %37, %38, %39, %40, %41, %42, %43, %44, %45, %46, %47, "
        "%48, %49, %50, %51, %52, %53, %54, %55, %56, %57, %58, %59, %60, %61, %62, %63}, "
        "{%64, %65, %66, %67}, %68, 1, 1, 1, 0;\n"
        : R8(d, OFF + 0), R8(d, OFF + 8), R8(d, OFF + 16), R8(d, OFF + 24), R8(d, OFF + 32), R8(d, OFF + 40), R8(d, OFF + 48), R8(d, OFF + 56)
        : "r"(a[0]), "r"(a[1]), "r"(a[2]), "r"(a[3]), "l"(descB));
}
template <int OFF> __device__ __forceinline__ void fence_half(float (&d)[128]) {
#pragma unroll
    for (int i = 0; i < 64; i++) asm volatile("" : "+f"(d[OFF + i]) :: "memory");
}

template <int Q0, int N> struct GateGroup { static constexpr int J = 2 * (Q0 ^ (N >> 1)) + (N & 1); };

template <int Q0, int N>
__device__ __forceinline__ void gate_mufu(float (&acc)[128]) {
    constexpr int J = GateGroup<Q0, N>::J;
#pragma unroll
    for (int i = 0; i < 16; i++) acc[16 * J + i] = tanh_fast(acc[16 * J + i]);
}
template <int Q0, int N>
__device__ __forceinline__ void gate_finish(float (&acc)[128], uint8_t* zdst) {
    constexpr int J = GateGroup<Q0, N>::J;
    uint32_t zp[4];
#pragma unroll
    for (int i = 0; i < 4; i++) {
        const int r = 16 * J + 4 * i;
        zp[i] = __vmaxu2(pack_bf16(acc[r] * fmaf(acc[r + 2], -0.5f, -0.5f), acc[r + 1] * fmaf(acc[r + 3], -0.5f, -0.5f)), 0x00010001u);
    }
    st_relaxed_v4(zdst + (J >> 1) * 65536 + (J & 1) * 8192, zp[0], zp[1], zp[2], zp[3]);
    if (N & 1) asm volatile("bar.arrive %0, 160;" ::"n"(2 + (N >> 1)) : "memory");
}

template <int Q0>
__device__ __forceinline__ void tail_gemm1(float (&acc)[128], uint32_t (&afr)[2][4][4], uint32_t sb, int ws, int wph, uint32_t a_lane_off,
                                           uint8_t* zdst, int lane, uint32_t zero) {
    constexpr int OA = (Q0 >> 1) * 64;
    constexpr int OB = 64 - OA;
    const uint32_t bars = sb + SM_BAR;
    uint32_t fa[4][4], fb[4][4], fc[4][4];
    const int ws0 = ws;
    auto wtile = [&](int tap) { return sb + SM_W + ((ws0 + tap) & (WST - 1)) * WBYTES + a_lane_off; };
    auto wwait = [&](int tap) {
        const int st = ws0 + tap;
        mbar_wait(bars + 8 * (BAR_WFULL + (st & (WST - 1))), wph ^ ((st >> 2) & 1));
    };
    auto load = [&](uint32_t (&f)[4][4], int tap) { load_w_frags(f, wtile(tap)); };
    auto issueA = [&](uint32_t (&f)[4][4], int tap) {
        const uint64_t db = make_desc(sb + SM_X + XBYTES + (8 - 2 * tap) * 128 + OA * 256, 16, 1024);
        wgmma_fence();
#pragma unroll
        for (int kk = 0; kk < 4; kk++) wgmma_m64n128k16_rs_half<OA>(acc, f[kk], db + kk * 2);
        wgmma_commit();
    };
    auto issueB = [&](uint32_t (&f)[4][4], int tap) {
        const uint64_t db = make_desc(sb + SM_X + XBYTES + (8 - 2 * tap) * 128 + OB * 256, 16, 1024);
        wgmma_fence();
#pragma unroll
        for (int kk = 0; kk < 4; kk++) wgmma_m64n128k16_rs_half<OB>(acc, f[kk], db + kk * 2);
        wgmma_commit();
    };
    mbar_wait(bars + 8 * (BAR_XFULL + 1), 1);
    wwait(0); load(fa, 0);
    __syncwarp();
    if (lane == 0) mbar_arrive(bars + 8 * (BAR_WEMPTY + ws0));
    wwait(1); load(fb, 1);
    wwait(2); load(fc, 2);
    scale_w_frags(fa); issueA(fa, 0); wgmma_wait<1>();
    wwait(3); load(afr[0], 3);
    scale_w_frags(fb); issueA(fb, 1);
    scale_w_frags(fc); issueA(fc, 2);
    wwait(4); load(afr[1], 4);
    scale_w_frags(afr[0]); issueA(afr[0], 3);
    scale_w_frags(afr[1]); issueA(afr[1], 4);
    if (threadIdx.x == 0) PROF(24);
    issueB(fa, 0);
    issueB(fb, 1);
    wgmma_wait<2>();
    fence_half<OA>(acc);
    sched_fence<0>(zero);
    gate_mufu<Q0, 0>(acc); gate_mufu<Q0, 1>(acc);
    gate_finish<Q0, 0>(acc, zdst); gate_finish<Q0, 1>(acc, zdst);
    sched_fence<1>(zero);
    issueB(fc, 2);
    issueB(afr[0], 3);
    sched_fence<2>(zero);
    gate_mufu<Q0, 2>(acc); gate_mufu<Q0, 3>(acc);
    sched_fence<3>(zero);
    issueB(afr[1], 4);
    sched_fence<4>(zero);
    gate_finish<Q0, 2>(acc, zdst); gate_finish<Q0, 3>(acc, zdst);
    wgmma_wait<0>();
    fence_half<OB>(acc);
    if (threadIdx.x == 0) PROF(3);
    gate_mufu<Q0, 4>(acc);
    gate_mufu<Q0, 5>(acc);
    gate_finish<Q0, 4>(acc, zdst);
    gate_finish<Q0, 5>(acc, zdst);
    sched_fence<5>(zero);
    gate_mufu<Q0, 6>(acc);
    gate_mufu<Q0, 7>(acc);
    gate_finish<Q0, 6>(acc, zdst);
    gate_finish<Q0, 7>(acc, zdst);
}

__device__ __forceinline__ void fetch_slot(int i, uint32_t sb, const uint8_t* zsrc, int q, int lane) {
    const uint32_t bars = sb + SM_BAR;
    asm volatile("bar.sync %0, 160;" ::"r"(2 + i) : "memory");
    if (lane == 0) {
        uint32_t t;
        asm volatile("mov.u32 %0, %%clock;" : "=r"(t) : "r"(lane) : "memory");
        const uint32_t delay = (i == 0) ? ZDELAY0 : (i == 1) ? ZDELAY1 : (i == 2) ? ZDELAY2 : ZDELAY3;
        while (clock_now() - t < delay) {}
        mbar_expect_tx(bars + 8 * (BAR_Z + i), 16384);
        bulk_load(sb + sm_zin(i), zsrc + (q ^ i) * 16384, 16384, bars + 8 * (BAR_Z + i));
        PROF(26 + i);
    }
    __syncwarp();
}

template <int I>
__device__ __forceinline__ void z_load(uint32_t (&z)[8][4], uint32_t sb, int warp, int lane) {
    mbar_wait(sb + SM_BAR + 8 * (BAR_Z + I), 0);
#pragma unroll
    for (int j = 0; j < 8; j++) ldsm_x4_trans(z[j], sb + sm_zin(I) + warp * 4096 + j * 512 + lane * 16);
}
__device__ __forceinline__ bool z_check(const uint32_t (&z)[8][4]) {
    uint32_t m0 = 0xFFFFFFFFu, m1 = 0xFFFFFFFFu;
#pragma unroll
    for (int j = 0; j < 8; j++) {
        m0 = __vimin3_u16x2(m0, z[j][0], z[j][1]);
        m1 = __vimin3_u16x2(m1, z[j][2], z[j][3]);
    }
    m0 = __vminu2(m0, m1);
    return __all_sync(0xffffffffu, ((m0 & 0xFFFFu) != 0u) && ((m0 >> 16) != 0u));
}
__device__ __forceinline__ void z_issue(float (&acc2)[64], uint32_t (&z)[8][4], uint32_t sb, int beta) {
#pragma unroll
    for (int j = 0; j < 8; j++) asm volatile("" : "+r"(z[j][0]), "+r"(z[j][1]), "+r"(z[j][2]), "+r"(z[j][3]) :: "memory");
    const uint64_t db = make_desc(sb + SM_WO + beta * 16384, 65536, 1024);
    wgmma_fence();
#pragma unroll
    for (int j = 0; j < 8; j++) wgmma_m64n128k16_rs(acc2, z[j], db + j * 128);
    wgmma_commit();
}
__device__ __forceinline__ bool wg_any(bool p) {
    uint32_t r;
    asm volatile("{\n.reg .pred a, b;\nsetp.ne.u32 a, %1, 0;\nbarrier.cta.red.or.aligned.pred b, 1, 128, a;\nselp.u32 %0, 1, 0, b;\n}\n"
                 : "=r"(r) : "r"((uint32_t)p) : "memory");
    return r != 0;
}
template <int I>
__device__ __forceinline__ void z_repair(float (&acc2)[64], uint32_t sb, const uint8_t* src, int beta, int warp, int lane, uint32_t mine,
                                         uint32_t& rph) {
    if (!wg_any(mine != 0u)) return;
    uint32_t z[8][4];
    if (mine) {
        const uint32_t zo = sb + sm_zin(I) + warp * 4096;
        const uint32_t zs = sb + SM_ZFIX + warp * 4096;
        const uint32_t bar = sb + SM_BAR + 8 * (BAR_RETRY + warp);
        int spins = 0;
        do {
            __syncwarp();
            if (lane == 0) {
                mbar_expect_tx(bar, 4096);
                bulk_load(zs, src, 4096, bar);
            }
            mbar_wait(bar, rph);
            rph ^= 1;
#pragma unroll
            for (int j = 0; j < 8; j++) ldsm_x4_trans(z[j], zs + j * 512 + lane * 16);
        } while (!z_check(z) && ++spins < (1 << 16));
#pragma unroll
        for (int j = 0; j < 8; j++) {
            uint32_t o[4];
            ldsm_x4_trans(o, zo + j * 512 + lane * 16);
#pragma unroll
            for (int k = 0; k < 4; k++) z[j][k] &= __vcmpeq2(o[k], 0u);
        }
    } else {
#pragma unroll
        for (int j = 0; j < 8; j++)
#pragma unroll
            for (int k = 0; k < 4; k++) z[j][k] = 0u;
    }
    z_issue(acc2, z, sb, beta);
    wgmma_wait<0>();
}

template <int H>
__device__ __forceinline__ void store_half(const float (&a)[64], const float (&b)[32], uint32_t stg, __nv_bfloat16* obase, int tbase, int lane) {
    const int row = lane & 15, csel = lane >> 4;
#pragma unroll
    for (int j2 = 0; j2 < 4; j2++) {
        const int j = 2 * j2, o = 32 * H + 4 * j;
        const uint32_t r0 = pack_bf16(a[o + 0] + b[4 * j + 0], a[o + 1] + b[4 * j + 1]);
        const uint32_t r1 = pack_bf16(a[o + 2] + b[4 * j + 2], a[o + 3] + b[4 * j + 3]);
        const uint32_t r2 = pack_bf16(a[o + 4] + b[4 * j + 4], a[o + 5] + b[4 * j + 5]);
        const uint32_t r3 = pack_bf16(a[o + 6] + b[4 * j + 6], a[o + 7] + b[4 * j + 7]);
        stsm_x4(stg + H * 2048 + row * 128 + (((j + csel) ^ (row & 7)) << 4), r0, r1, r2, r3);
    }
    __syncwarp();
#pragma unroll
    for (int i = 0; i < 4; i++) {
        const int r = 4 * i + (lane >> 3);
        const int ch = lane & 7;
        const int tok = tbase + ((r & 7) >> 1) * 8 + (r >> 3) * 2 + (r & 1);
        uint4 v;
        asm volatile("ld.shared.v4.b32 {%0, %1, %2, %3}, [%4];" : "=r"(v.x), "=r"(v.y), "=r"(v.z), "=r"(v.w)
                     : "r"(stg + H * 2048 + r * 128 + ((ch ^ (r & 7)) << 4)) : "memory");
        if (tok < T_LEN) *reinterpret_cast<uint4*>(obase + (size_t)tok * D_CH + H * 64 + ch * 8) = v;
    }
}

__global__ void __launch_bounds__(NTHREADS, 1)
wavenet_fused_kernel(const __grid_constant__ CUtensorMap mapX, const __grid_constant__ CUtensorMap mapW,
                     const __grid_constant__ CUtensorMap mapWo, __nv_bfloat16* __restrict__ out, const uint32_t zero) {
    extern __shared__ __align__(1024) uint8_t smem_raw[];
    const uint32_t sb = smem_u32(smem_raw);
    const uint32_t bars = sb + SM_BAR;
    const int warp = threadIdx.x >> 5;
    const int lane = threadIdx.x & 31;
    const int cg = blockIdx.x & 15;
    const int tt = blockIdx.x >> 4;
    const int batch = tt >> 2;
    const int t0 = (tt & 3) * NTOK;
    const int c4 = cg & 3, q = cg >> 2;

    if (threadIdx.x == 160) {
        prefetch_tmap(&mapW);
        prefetch_tmap(&mapX);
    }
    if (threadIdx.x == 128) {
        PROFG(0);
        const uint32_t xf = bars + 8 * BAR_XFULL;
        mbar_init(xf, 1);
        mbar_init(bars + 8 * BAR_WFULL, 1);
        asm volatile("fence.mbarrier_init.release.cluster;" ::: "memory");
        fence_proxy_async_smem();
        mbar_expect_tx(bars + 8 * BAR_WFULL, WBYTES);
        tma_load_3d(sb + SM_W, &mapW, bars + 8 * BAR_WFULL, cg * 32, 0, 0);
        mbar_expect_tx(xf, XBYTES);
#pragma unroll
        for (int j = 0; j < 3; j++) tma_load_3d(sb + SM_X + j * XBOX * 128, &mapX, xf, 0, t0 - 8 + j * XBOX, batch);
        for (int i = 1; i < WST; i++) mbar_init(bars + 8 * (BAR_WFULL + i), 1);
        asm volatile("fence.mbarrier_init.release.cluster;" ::: "memory");
        fence_proxy_async_smem();
#pragma unroll
        for (int i = 1; i < WST; i++) {
            mbar_expect_tx(bars + 8 * (BAR_WFULL + i), WBYTES);
            tma_load_3d(sb + SM_W + i * WBYTES, &mapW, bars + 8 * (BAR_WFULL + i), cg * 32, i * 512, 0);
        }
    } else if (threadIdx.x == 0) {
        for (int i = 0; i < WST; i++) mbar_init(bars + 8 * (BAR_WEMPTY + i), 4);
        mbar_init(bars + 8 * (BAR_XFULL + 1), 1);
        for (int i = 0; i < XST; i++) mbar_init(bars + 8 * (BAR_XEMPTY + i), 4);
        mbar_init(bars + 8 * BAR_WO, 1);
        mbar_init(bars + 8 * BAR_PAR, 1);
        for (int i = 0; i < 4; i++) {
            mbar_init(bars + 8 * (BAR_Z + i), 1);
            mbar_init(bars + 8 * (BAR_RETRY + i), 1);
        }
        asm volatile("fence.mbarrier_init.release.cluster;" ::: "memory");
    }
    __syncthreads();

    if (warp >= 4) {
        if (warp == 4) {
            if (lane == 0) {
                int ws = 0, wph = 0;
                for (int kc = 0; kc < 8; kc++) {
                    const int xs = kc & 1;
                    if (kc > 0) {
                        mbar_wait(bars + 8 * (BAR_XEMPTY + xs), ((kc >> 1) & 1) ^ 1);
                        const uint32_t xf = bars + 8 * (BAR_XFULL + xs);
                        mbar_expect_tx(xf, XBYTES);
                        const uint32_t xd = sb + SM_X + xs * XBYTES;
#pragma unroll
                        for (int j = 0; j < 3; j++) tma_load_3d(xd + j * XBOX * 128, &mapX, xf, kc * 64, t0 - 8 + j * XBOX, batch);
                    } else {
                        prefetch_tmap(&mapWo);
                    }
                    for (int tap = (kc == 0 ? WST : 0); tap < 5; tap++) {
                        mbar_wait(bars + 8 * (BAR_WEMPTY + ws), wph);
                        const uint32_t wf = bars + 8 * (BAR_WFULL + ws);
                        mbar_expect_tx(wf, WBYTES);
                        tma_load_3d(sb + SM_W + ws * WBYTES, &mapW, wf, cg * 32, tap * 512 + kc * 64, 0);
                        if (++ws == WST) { ws = 0; wph ^= 1; }
                        const int it = kc * 5 + tap - 10;
                        if (it >= 0 && it < 16) {
                            const uint32_t wob = bars + 8 * BAR_WO;
                            if (it == 0) mbar_expect_tx(wob, WO_BYTES);
                            tma_load_2d(sb + SM_WO + (it & 1) * 65536 + (it >> 1) * 8192, &mapWo, wob, c4 * 128 + (it & 1) * 64, (it >> 1) * 64);
                        }
                    }
                }
            }
            __syncwarp();
        } else if (warp == 5) {
            unsigned int par = 0;
            if (lane == 0) par = (atomicAdd(&g_ticket, 1u) >> 7) & 1u;
            par = __shfl_sync(0xffffffffu, par, 0);
            __nanosleep(1500);
            uint4* mine = &g_zx[par][tt * 4 * 4096 + q * 1024 + 2 * c4 * 32];
#pragma unroll 1
            for (int i = 0; i < 32; i++) {
                mine[(i >> 3) * 4096 + ((i >> 1) & 3) * 256 + (i & 1) * 32 + lane] = make_uint4(0u, 0u, 0u, 0u);
                __nanosleep(100);
            }
            __syncwarp();
            if (lane == 0) {
                asm volatile("st.shared.u32 [%0], %1;" ::"r"(sb + SM_PAR), "r"(par) : "memory");
                mbar_arrive(bars + 8 * BAR_PAR);
            }
            uint4* clr = &g_zx[par ^ 1][blockIdx.x * 1024];
#pragma unroll 1
            for (int i = 0; i < 32; i++) {
                clr[i * 32 + lane] = make_uint4(0u, 0u, 0u, 0u);
                __nanosleep(100);
            }
        }
        mbar_wait(bars + 8 * BAR_PAR, 0);
        uint32_t par;
        asm volatile("ld.shared.u32 %0, [%1];" : "=r"(par) : "r"(sb + SM_PAR) : "memory");
        const uint8_t* zsrc = reinterpret_cast<const uint8_t*>(&g_zx[par][(tt * 4 + q) * 4096]);
        fetch_slot(7 - warp, sb, zsrc, q, lane);
    } else {
        float acc[128];
#pragma unroll
        for (int i = 0; i < 128; i++) acc[i] = 0.f;
        uint32_t afr[2][4][4];
        const int lk = ((lane >> 4) << 3) + (lane & 7);
        const uint32_t a_lane_off = ((lane >> 3) & 1) * 4096 + lk * 64 + ((warp ^ ((lk >> 1) & 3)) << 4);
        int ws = 0, wph = 0;
        uint32_t par = 0;
        if (threadIdx.x == 0) PROF(1);
#pragma unroll 1
        for (int kc2 = 0; kc2 < 4; kc2++) {
#pragma unroll
            for (int u = 0; u < 10; u++) {
                const int xs = u / 5;
                const int tap = u % 5;
                if (u == 5 && kc2 == 3) break;
                if (tap == 0) mbar_wait(bars + 8 * (BAR_XFULL + xs), kc2 & 1);
                mbar_wait(bars + 8 * (BAR_WFULL + ws), wph);
                if (kc2 == 0 && u == 0 && threadIdx.x == 0) PROF(2);
                const uint32_t wa = sb + SM_W + ws * WBYTES + a_lane_off;
                load_w_frags(afr[u & 1], wa);
                __syncwarp();
                if (lane == 0) mbar_arrive(bars + 8 * (BAR_WEMPTY + ws));
                scale_w_frags(afr[u & 1]);
                if (++ws == WST) { ws = 0; wph ^= 1; }
                const uint64_t db = make_desc(sb + SM_X + xs * XBYTES + (8 - 2 * tap) * 128, 16, 1024);
                wgmma_fence();
#pragma unroll
                for (int kk = 0; kk < 4; kk++) {
                    wgmma_m64n128k16_rs_half<0>(acc, afr[u & 1][kk], db + kk * 2);
                    wgmma_m64n128k16_rs_half<64>(acc, afr[u & 1][kk], db + kk * 2 + 1024);
                }
                wgmma_commit();
                if (u == 2 && kc2 == 3) {
                    mbar_wait(bars + 8 * BAR_PAR, 0);
                    asm volatile("ld.shared.u32 %0, [%1];" : "=r"(par) : "r"(sb + SM_PAR) : "memory");
                    mbar_wait(bars + 8 * BAR_WO, 0);
                }
                wgmma_wait<1>();
                if (tap == 0 && (u > 0 || kc2 > 0)) {
                    if (lane == 0) mbar_arrive(bars + 8 * (BAR_XEMPTY + (xs ^ 1)));
                }
            }
        }
        uint8_t* zx = reinterpret_cast<uint8_t*>(&g_zx[par][tt * 4 * 4096]);
        uint8_t* zdst = zx + q * 16384 + (2 * c4 + (warp >> 1)) * 512 + (warp & 1) * 256 +
                        ((lane >> 1) & 1) * 4096 + (lane & 1) * 128 + (lane >> 2) * 16;
        switch (q) {
            case 0: tail_gemm1<0>(acc, afr, sb, ws, wph, a_lane_off, zdst, lane, zero); break;
            case 1: tail_gemm1<1>(acc, afr, sb, ws, wph, a_lane_off, zdst, lane, zero); break;
            case 2: tail_gemm1<2>(acc, afr, sb, ws, wph, a_lane_off, zdst, lane, zero); break;
            default: tail_gemm1<3>(acc, afr, sb, ws, wph, a_lane_off, zdst, lane, zero); break;
        }
        if (threadIdx.x == 0) PROF(4);

        float acc2[64], acc3a[32], acc3b[32];
#pragma unroll
        for (int i = 0; i < 64; i++) acc2[i] = 0.f;
        uint32_t bad;
        {
            uint32_t za[3][8][4];
            z_load<0>(za[0], sb, warp, lane);
            if (threadIdx.x == 0) PROF(12);
            z_issue(acc2, za[0], sb, q ^ 0);
            z_load<1>(za[1], sb, warp, lane);
            bad = z_check(za[0]) ? 0u : 1u;
            if (threadIdx.x == 0) PROF(13);
            z_issue(acc2, za[1], sb, q ^ 1);
            z_load<2>(za[2], sb, warp, lane);
            bad |= z_check(za[1]) ? 0u : 2u;
            if (threadIdx.x == 0) PROF(14);
            z_issue(acc2, za[2], sb, q ^ 2);
            wgmma_wait<2>();
            z_load<3>(za[0], sb, warp, lane);
            bad |= z_check(za[2]) ? 0u : 4u;
            if (threadIdx.x == 0) PROF(15);
#pragma unroll
            for (int j = 0; j < 8; j++) asm volatile("" : "+r"(za[0][j][0]), "+r"(za[0][j][1]), "+r"(za[0][j][2]), "+r"(za[0][j][3]) :: "memory");
            const uint64_t db = make_desc(sb + SM_WO + (q ^ 3) * 16384, 65536, 1024);
            wgmma_fence();
#pragma unroll
            for (int j = 0; j < 8; j++) wgmma_m64n64k16_rs(acc3a, za[0][j], db + j * 128, j);
            wgmma_commit();
#pragma unroll
            for (int j = 0; j < 8; j++) wgmma_m64n64k16_rs(acc3b, za[0][j], db + j * 128 + 4096, j);
            wgmma_commit();
            sched_fence<7>(zero);
            bad |= z_check(za[0]) ? 0u : 8u;
        }
        const uint32_t stg = sb + SM_OSTG + warp * 4096;
        const int tbase = t0 + q * 64 + (warp >> 1) * 32 + (warp & 1) * 4;
        __nv_bfloat16* obase = out + (size_t)batch * T_LEN * D_CH + c4 * 128;
        wgmma_wait<1>();
        fence_regs(acc2);
        fence_regs(acc3a);
        if (threadIdx.x == 0) PROF(10);
        store_half<0>(acc2, acc3a, stg, obase, tbase, lane);
        wgmma_wait<0>();
        fence_regs(acc3b);
        store_half<1>(acc2, acc3b, stg, obase, tbase, lane);
        if (__builtin_expect(wg_any(bad != 0u), 0)) {
            const uint8_t* zsrc = zx + q * 65536 + warp * 4096;
            uint32_t rph = 0;
            z_repair<0>(acc2, sb, zsrc + (q ^ 0) * 16384, q ^ 0, warp, lane, bad & 1u, rph);
            z_repair<1>(acc2, sb, zsrc + (q ^ 1) * 16384, q ^ 1, warp, lane, bad & 2u, rph);
            z_repair<2>(acc2, sb, zsrc + (q ^ 2) * 16384, q ^ 2, warp, lane, bad & 4u, rph);
            z_repair<3>(acc2, sb, zsrc + (q ^ 3) * 16384, q ^ 3, warp, lane, bad & 8u, rph);
            fence_regs(acc2);
            __syncwarp();
            store_half<0>(acc2, acc3a, stg, obase, tbase, lane);
            store_half<1>(acc2, acc3b, stg, obase, tbase, lane);
        }
        if (threadIdx.x == 0) PROFG(11);
    }
}

typedef CUresult (*EncodeFn)(CUtensorMap*, CUtensorMapDataType, cuuint32_t, void*, const cuuint64_t*, const cuuint64_t*,
                             const cuuint32_t*, const cuuint32_t*, CUtensorMapInterleave, CUtensorMapSwizzle,
                             CUtensorMapL2promotion, CUtensorMapFloatOOBfill);

void encode(EncodeFn fn, CUtensorMap* m, const void* ptr, int rank, const cuuint64_t* dims, const cuuint64_t* strides,
            const cuuint32_t* box, CUtensorMapSwizzle sw) {
    cuuint32_t es[3] = {1, 1, 1};
    fn(m, CU_TENSOR_MAP_DATA_TYPE_BFLOAT16, rank, const_cast<void*>(ptr), dims, strides, box, es,
       CU_TENSOR_MAP_INTERLEAVE_NONE, sw, CU_TENSOR_MAP_L2_PROMOTION_L2_128B, CU_TENSOR_MAP_FLOAT_OOB_FILL_NONE);
}

}

extern "C" void kernel_launch(void* const* d_in, const int* in_sizes, int n_in, void* d_out, int out_size) {
    (void)in_sizes; (void)n_in; (void)out_size;
    static EncodeFn enc = nullptr;
    if (!enc) {
        void* fn = nullptr;
        cudaDriverEntryPointQueryResult qr;
        cudaGetDriverEntryPoint("cuTensorMapEncodeTiled", &fn, cudaEnableDefault, &qr);
        enc = (EncodeFn)fn;
        cudaFuncSetAttribute(wavenet_fused_kernel, cudaFuncAttributeMaxDynamicSharedMemorySize, SM_TOTAL);
    }
    CUtensorMap mX, mW, mWo;
    {
        cuuint64_t dims[3] = {512, (cuuint64_t)T_LEN, 2}, str[2] = {1024, (cuuint64_t)T_LEN * 1024};
        cuuint32_t box[3] = {64, XBOX, 1};
        encode(enc, &mX, d_in[0], 3, dims, str, box, CU_TENSOR_MAP_SWIZZLE_128B);
    }
    {
        cuuint64_t dims[3] = {512, 2560, 2}, str[2] = {2048, 1024};
        cuuint32_t box[3] = {32, 64, 2};
        encode(enc, &mW, d_in[1], 3, dims, str, box, CU_TENSOR_MAP_SWIZZLE_64B);
    }
    {
        cuuint64_t dims[2] = {512, 512}, str[1] = {1024};
        cuuint32_t box[2] = {64, 64};
        encode(enc, &mWo, d_in[2], 2, dims, str, box, CU_TENSOR_MAP_SWIZZLE_128B);
    }
    wavenet_fused_kernel<<<128, NTHREADS, SM_TOTAL>>>(mX, mW, mWo, (__nv_bfloat16*)d_out, 0u);
}
```

```cpp
#include <cuda_runtime.h>
#include <cuda_bf16.h>
#include <cuda.h>
#include <stdint.h>

namespace {

constexpr int T_LEN   = 1000;
constexpr int D_CH    = 512;
constexpr int NTOK    = 256;
constexpr int XROWS   = NTOK + 8;
constexpr int XBYTES  = XROWS * 128;
constexpr int XBOX    = 88;
constexpr int XST     = 2;
constexpr int WST     = 4;
constexpr int WBYTES  = 8192;
constexpr int WO_BYTES = 131072;

constexpr int SM_WO   = 0;
constexpr int SM_X    = SM_WO + WO_BYTES;
constexpr int SM_W    = SM_X + XST * XBYTES;
constexpr int SM_BAR  = SM_W + WST * WBYTES;
constexpr int SM_TOTAL = SM_BAR + 256;
__host__ __device__ constexpr int sm_zin(int i) { return SM_X + (i >> 1) * XBYTES + (i & 1) * 16384; }
constexpr int SM_OSTG  = SM_W;
constexpr int SM_ZFIX  = SM_W + 16384;

constexpr int BAR_WFULL  = 0;
constexpr int BAR_WEMPTY = BAR_WFULL + WST;
constexpr int BAR_XFULL  = BAR_WEMPTY + WST;
constexpr int BAR_XEMPTY = BAR_XFULL + XST;
constexpr int BAR_WO     = BAR_XEMPTY + XST;
constexpr int BAR_PAR    = BAR_WO + 1;
constexpr int BAR_Z      = BAR_PAR + 1;
constexpr int BAR_RETRY  = BAR_Z + 4;

constexpr int SM_PAR   = SM_BAR + 240;
constexpr int NTHREADS = 256;
#define ZDELAY0 650
#define ZDELAY1 600
#define ZDELAY2 650
#define ZDELAY3 600

__device__ uint4 g_zx[2][8 * 4 * 4096];
__device__ unsigned int g_ticket;

#define PROF(i)
#define PROFG(i)

__device__ __forceinline__ uint32_t smem_u32(const void* p) { return (uint32_t)__cvta_generic_to_shared(p); }

__device__ __forceinline__ void mbar_init(uint32_t bar, uint32_t cnt) {
    asm volatile("mbarrier.init.shared::cta.b64 [%0], %1;" ::"r"(bar), "r"(cnt));
}
__device__ __forceinline__ void mbar_expect_tx(uint32_t bar, uint32_t bytes) {
    asm volatile("mbarrier.arrive.expect_tx.shared::cta.b64 _, [%0], %1;" ::"r"(bar), "r"(bytes) : "memory");
}
__device__ __forceinline__ void mbar_arrive(uint32_t bar) {
    asm volatile("mbarrier.arrive.shared::cta.b64 _, [%0];" ::"r"(bar) : "memory");
}
__device__ __forceinline__ void mbar_wait(uint32_t bar, uint32_t parity) {
    asm volatile(
        "{\n"
        ".reg .pred p;\n"
        "WAIT_LOOP:\n"
        "mbarrier.try_wait.parity.shared::cta.b64 p, [%0], %1;\n"
        "@p bra WAIT_DONE;\n"
        "bra WAIT_LOOP;\n"
        "WAIT_DONE:\n"
        "}\n" ::"r"(bar), "r"(parity) : "memory");
}
__device__ __forceinline__ void tma_load_3d(uint32_t dst, const CUtensorMap* m, uint32_t bar, int c0, int c1, int c2) {
    asm volatile("cp.async.bulk.tensor.3d.shared::cluster.global.mbarrier::complete_tx::bytes [%0], [%1, {%3, %4, %5}], [%2];"
                 ::"r"(dst), "l"(m), "r"(bar), "r"(c0), "r"(c1), "r"(c2) : "memory");
}
__device__ __forceinline__ void tma_load_2d(uint32_t dst, const CUtensorMap* m, uint32_t bar, int c0, int c1) {
    asm volatile("cp.async.bulk.tensor.2d.shared::cluster.global.mbarrier::complete_tx::bytes [%0], [%1, {%3, %4}], [%2];"
                 ::"r"(dst), "l"(m), "r"(bar), "r"(c0), "r"(c1) : "memory");
}
__device__ __forceinline__ void fence_proxy_async_smem() { asm volatile("fence.proxy.async.shared::cta;" ::: "memory"); }
__device__ __forceinline__ void prefetch_tmap(const CUtensorMap* m) {
    asm volatile("prefetch.tensormap [%0];" ::"l"(m) : "memory");
}
__device__ __forceinline__ void wgmma_fence() { asm volatile("wgmma.fence.sync.aligned;" ::: "memory"); }
__device__ __forceinline__ void wgmma_commit() { asm volatile("wgmma.commit_group.sync.aligned;" ::: "memory"); }
template <int N> __device__ __forceinline__ void wgmma_wait() {
    asm volatile("wgmma.wait_group.sync.aligned %0;" ::"n"(N) : "memory");
}
template <int N> __device__ __forceinline__ void fence_regs(float (&d)[N]) {
#pragma unroll
    for (int i = 0; i < N; i++) asm volatile("" : "+f"(d[i]) :: "memory");
}
__device__ __forceinline__ void ldsm_x4_trans(uint32_t (&r)[4], uint32_t addr) {
    asm volatile("ldmatrix.sync.aligned.m8n8.x4.trans.shared.b16 {%0, %1, %2, %3}, [%4];"
                 : "=r"(r[0]), "=r"(r[1]), "=r"(r[2]), "=r"(r[3]) : "r"(addr) : "memory");
}
__device__ __forceinline__ void stsm_x4(uint32_t addr, uint32_t a, uint32_t b, uint32_t c, uint32_t d) {
    asm volatile("stmatrix.sync.aligned.m8n8.x4.shared.b16 [%0], {%1, %2, %3, %4};"
                 ::"r"(addr), "r"(a), "r"(b), "r"(c), "r"(d) : "memory");
}
__device__ __forceinline__ void st_relaxed_v4(void* p, uint32_t a, uint32_t b, uint32_t c, uint32_t d) {
    asm volatile("st.relaxed.gpu.global.v4.b32 [%0], {%1, %2, %3, %4};" ::"l"(p), "r"(a), "r"(b), "r"(c), "r"(d) : "memory");
}
__device__ __forceinline__ void bulk_load(uint32_t dst, const void* src, uint32_t bytes, uint32_t bar) {
    asm volatile("cp.async.bulk.shared::cluster.global.mbarrier::complete_tx::bytes [%0], [%1], %2, [%3];"
                 ::"r"(dst), "l"(src), "r"(bytes), "r"(bar) : "memory");
}
__device__ __forceinline__ uint32_t clock_now() {
    uint32_t t;
    asm volatile("mov.u32 %0, %%clock;" : "=r"(t) :: "memory");
    return t;
}
template <int BIT>
__device__ __forceinline__ void sched_fence(uint32_t zero) {
    asm volatile("{\n.reg .pred p;\n.reg .b32 t;\nand.b32 t, %0, %1;\nsetp.eq.u32 p, t, 0;\n@p bra SF_DONE;\ntrap;\nSF_DONE:\n}\n"
                 ::"r"(zero), "n"(1u << BIT) : "memory");
}
__device__ __forceinline__ float tanh_fast(float x) {
    float y;
    asm volatile("tanh.approx.f32 %0, %1;" : "=f"(y) : "f"(x));
    return y;
}
__device__ __forceinline__ void load_w_frags(uint32_t (&f)[4][4], uint32_t wa) {
#pragma unroll
    for (int kk = 0; kk < 4; kk++) ldsm_x4_trans(f[kk], wa + kk * 1024);
}
__device__ __forceinline__ void scale_w_frags(uint32_t (&f)[4][4]) {
#pragma unroll
    for (int kk = 0; kk < 4; kk++) {
        asm volatile("mul.rn.bf16x2 %0, %0, %1;" : "+r"(f[kk][1]) : "r"(0x3F003F00u));
        asm volatile("mul.rn.bf16x2 %0, %0, %1;" : "+r"(f[kk][3]) : "r"(0x3F003F00u));
    }
}
__device__ __forceinline__ uint32_t pack_bf16(float lo, float hi) {
    uint32_t r;
    asm("cvt.rn.bf16x2.f32 %0, %1, %2;" : "=r"(r) : "f"(hi), "f"(lo));
    return r;
}
__device__ __forceinline__ uint64_t make_desc(uint32_t addr, uint32_t lbo_bytes, uint32_t sbo_bytes) {
    return (uint64_t)((addr & 0x3FFFF) >> 4) | ((uint64_t)(lbo_bytes >> 4) << 16) | ((uint64_t)(sbo_bytes >> 4) << 32) |
           ((uint64_t)1 << 62);
}

#define R8(d, o) "+f"(d[o + 0]), "+f"(d[o + 1]), "+f"(d[o + 2]), "+f"(d[o + 3]), "+f"(d[o + 4]), "+f"(d[o + 5]), "+f"(d[o + 6]), "+f"(d[o + 7])

__device__ __forceinline__ void wgmma_m64n128k16_rs(float (&d)[64], const uint32_t (&a)[4], uint64_t descB) {
    asm volatile(
        "wgmma.mma_async.sync.aligned.m64n128k16.f32.bf16.bf16 "
        "{%0, %1, %2, %3, %4, %5, %6, %7, %8, %9, %10, %11, %12, %13, %14, %15, "
        "%16, %17, %18, %19, %20, %21, %22, %23, %24, %25, %26, %27, %28, %29, %30, %31, "
        "%32, %33, %34, %35, %36, %37, %38, %39, %40, %41, %42, %43, %44, %45, %46, %47, "
        "%48, %49, %50, %51, %52, %53, %54, %55, %56, %57, %58, %59, %60, %61, %62, %63}, "
        "{%64, %65, %66, %67}, %68, 1, -1, 1, 1;\n"
        : R8(d, 0), R8(d, 8), R8(d, 16), R8(d, 24), R8(d, 32), R8(d, 40), R8(d, 48), R8(d, 56)
        : "r"(a[0]), "r"(a[1]), "r"(a[2]), "r"(a[3]), "l"(descB));
}

__device__ __forceinline__ void wgmma_m64n64k16_rs(float (&d)[32], const uint32_t (&a)[4], uint64_t descB, int scale_d) {
    asm volatile(
        "{\n"
        ".reg .pred p;\n"
        "setp.ne.b32 p, %37, 0;\n"
        "wgmma.mma_async.sync.aligned.m64n64k16.f32.bf16.bf16 "
        "{%0, %1, %2, %3, %4, %5, %6, %7, %8, %9, %10, %11, %12, %13, %14, %15, "
        "%16, %17, %18, %19, %20, %21, %22, %23, %24, %25, %26, %27, %28, %29, %30, %31}, "
        "{%32, %33, %34, %35}, %36, p, -1, 1, 1;\n"
        "}\n"
        : R8(d, 0), R8(d, 8), R8(d, 16), R8(d, 24)
        : "r"(a[0]), "r"(a[1]), "r"(a[2]), "r"(a[3]), "l"(descB), "r"(scale_d));
}

template <int OFF>
__device__ __forceinline__ void wgmma_m64n128k16_rs_half(float (&d)[128], const uint32_t (&a)[4], uint64_t descB) {
    asm volatile(
        "wgmma.mma_async.sync.aligned.m64n128k16.f32.bf16.bf16 "
        "{%0, %1, %2, %3, %4, %5, %6, %7, %8, %9, %10, %11, %12, %13, %14, %15, "
        "%16, %17, %18, %19, %20, %21, %22, %23, %24, %25, %26, %27, %28, %29, %30, %31, "
        "%32, %33, %34, %35, %36, %37, %38, %39, %40, %41, %42, %43, %44, %45, %46, %47, "
        "%48, %49, %50, %51, %52, %53, %54, %55, %56, %57, %58, %59, %60, %61, %62, %63}, "
        "{%64, %65, %66, %67}, %68, 1, 1, 1, 0;\n"
        : R8(d, OFF + 0), R8(d, OFF + 8), R8(d, OFF + 16), R8(d, OFF + 24), R8(d, OFF + 32), R8(d, OFF + 40), R8(d, OFF + 48), R8(d, OFF + 56)
        : "r"(a[0]), "r"(a[1]), "r"(a[2]), "r"(a[3]), "l"(descB));
}
template <int OFF> __device__ __forceinline__ void fence_half(float (&d)[128]) {
#pragma unroll
    for (int i = 0; i < 64; i++) asm volatile("" : "+f"(d[OFF + i]) :: "memory");
}

template <int Q0, int N> struct GateGroup { static constexpr int J = 2 * (Q0 ^ (N >> 1)) + (N & 1); };

template <int Q0, int N>
__device__ __forceinline__ void gate_mufu(float (&acc)[128]) {
    constexpr int J = GateGroup<Q0, N>::J;
#pragma unroll
    for (int i = 0; i < 16; i++) acc[16 * J + i] = tanh_fast(acc[16 * J + i]);
}
template <int Q0, int N>
__device__ __forceinline__ void gate_finish(float (&acc)[128], uint8_t* zdst) {
    constexpr int J = GateGroup<Q0, N>::J;
    uint32_t zp[4];
#pragma unroll
    for (int i = 0; i < 4; i++) {
        const int r = 16 * J + 4 * i;
        zp[i] = __vmaxu2(pack_bf16(acc[r] * fmaf(acc[r + 2], -0.5f, -0.5f), acc[r + 1] * fmaf(acc[r + 3], -0.5f, -0.5f)), 0x00010001u);
    }
    st_relaxed_v4(zdst + (J >> 1) * 65536 + (J & 1) * 8192, zp[0], zp[1], zp[2], zp[3]);
    if (N & 1) asm volatile("bar.arrive %0, 160;" ::"n"(2 + (N >> 1)) : "memory");
}

template <int Q0>
__device__ __forceinline__ void tail_gemm1(float (&acc)[128], uint32_t (&afr)[2][4][4], uint32_t sb, int ws, int wph, uint32_t a_lane_off,
                                           uint8_t* zdst, int lane, uint32_t zero) {
    constexpr int OA = (Q0 >> 1) * 64;
    constexpr int OB = 64 - OA;
    const uint32_t bars = sb + SM_BAR;
    uint32_t fa[4][4], fb[4][4], fc[4][4];
    const int ws0 = ws;
    auto wtile = [&](int tap) { return sb + SM_W + ((ws0 + tap) & (WST - 1)) * WBYTES + a_lane_off; };
    auto wwait = [&](int tap) {
        const int st = ws0 + tap;
        mbar_wait(bars + 8 * (BAR_WFULL + (st & (WST - 1))), wph ^ ((st >> 2) & 1));
    };
    auto load = [&](uint32_t (&f)[4][4], int tap) { load_w_frags(f, wtile(tap)); };
    auto issueA = [&](uint32_t (&f)[4][4], int tap) {
        const uint64_t db = make_desc(sb + SM_X + XBYTES + (8 - 2 * tap) * 128 + OA * 256, 16, 1024);
        wgmma_fence();
#pragma unroll
        for (int kk = 0; kk < 4; kk++) wgmma_m64n128k16_rs_half<OA>(acc, f[kk], db + kk * 2);
        wgmma_commit();
    };
    auto issueB = [&](uint32_t (&f)[4][4], int tap) {
        const uint64_t db = make_desc(sb + SM_X + XBYTES + (8 - 2 * tap) * 128 + OB * 256, 16, 1024);
        wgmma_fence();
#pragma unroll
        for (int kk = 0; kk < 4; kk++) wgmma_m64n128k16_rs_half<OB>(acc, f[kk], db + kk * 2);
        wgmma_commit();
    };
    mbar_wait(bars + 8 * (BAR_XFULL + 1), 1);
    wwait(0); load(fa, 0);
    __syncwarp();
    if (lane == 0) mbar_arrive(bars + 8 * (BAR_WEMPTY + ws0));
    wwait(1); load(fb, 1);
    wwait(2); load(fc, 2);
    scale_w_frags(fa); issueA(fa, 0); wgmma_wait<1>();
    wwait(3); load(afr[0], 3);
    scale_w_frags(fb); issueA(fb, 1);
    scale_w_frags(fc); issueA(fc, 2);
    wwait(4); load(afr[1], 4);
    scale_w_frags(afr[0]); issueA(afr[0], 3);
    scale_w_frags(afr[1]); issueA(afr[1], 4);
    if (threadIdx.x == 0) PROF(24);
    issueB(fa, 0);
    issueB(fb, 1);
    wgmma_wait<2>();
    fence_half<OA>(acc);
    sched_fence<0>(zero);
    gate_mufu<Q0, 0>(acc); gate_mufu<Q0, 1>(acc);
    gate_finish<Q0, 0>(acc, zdst); gate_finish<Q0, 1>(acc, zdst);
    sched_fence<1>(zero);
    issueB(fc, 2);
    issueB(afr[0], 3);
    sched_fence<2>(zero);
    gate_mufu<Q0, 2>(acc); gate_mufu<Q0, 3>(acc);
    sched_fence<3>(zero);
    issueB(afr[1], 4);
    sched_fence<4>(zero);
    gate_finish<Q0, 2>(acc, zdst); gate_finish<Q0, 3>(acc, zdst);
    wgmma_wait<0>();
    fence_half<OB>(acc);
    if (threadIdx.x == 0) PROF(3);
    gate_mufu<Q0, 4>(acc);
    gate_mufu<Q0, 5>(acc);
    gate_finish<Q0, 4>(acc, zdst);
    gate_finish<Q0, 5>(acc, zdst);
    sched_fence<5>(zero);
    gate_mufu<Q0, 6>(acc);
    gate_mufu<Q0, 7>(acc);
    gate_finish<Q0, 6>(acc, zdst);
    gate_finish<Q0, 7>(acc, zdst);
}

__device__ __forceinline__ void fetch_slot(int i, uint32_t sb, const uint8_t* zsrc, int q, int lane) {
    const uint32_t bars = sb + SM_BAR;
    asm volatile("bar.sync %0, 160;" ::"r"(2 + i) : "memory");
    if (lane == 0) {
        uint32_t t;
        asm volatile("mov.u32 %0, %%clock;" : "=r"(t) : "r"(lane) : "memory");
        const uint32_t delay = (i == 0) ? ZDELAY0 : (i == 1) ? ZDELAY1 : (i == 2) ? ZDELAY2 : ZDELAY3;
        while (clock_now() - t < delay) {}
        mbar_expect_tx(bars + 8 * (BAR_Z + i), 16384);
        bulk_load(sb + sm_zin(i), zsrc + (q ^ i) * 16384, 16384, bars + 8 * (BAR_Z + i));
        PROF(26 + i);
    }
    __syncwarp();
}

template <int I>
__device__ __forceinline__ void z_load(uint32_t (&z)[8][4], uint32_t sb, int warp, int lane) {
    mbar_wait(sb + SM_BAR + 8 * (BAR_Z + I), 0);
#pragma unroll
    for (int j = 0; j < 8; j++) ldsm_x4_trans(z[j], sb + sm_zin(I) + warp * 4096 + j * 512 + lane * 16);
}
__device__ __forceinline__ bool z_check(const uint32_t (&z)[8][4]) {
    uint32_t m0 = 0xFFFFFFFFu, m1 = 0xFFFFFFFFu;
#pragma unroll
    for (int j = 0; j < 8; j++) {
        m0 = __vimin3_u16x2(m0, z[j][0], z[j][1]);
        m1 = __vimin3_u16x2(m1, z[j][2], z[j][3]);
    }
    m0 = __vminu2(m0, m1);
    return __all_sync(0xffffffffu, ((m0 & 0xFFFFu) != 0u) && ((m0 >> 16) != 0u));
}
__device__ __forceinline__ void z_issue(float (&acc2)[64], uint32_t (&z)[8][4], uint32_t sb, int beta) {
#pragma unroll
    for (int j = 0; j < 8; j++) asm volatile("" : "+r"(z[j][0]), "+r"(z[j][1]), "+r"(z[j][2]), "+r"(z[j][3]) :: "memory");
    const uint64_t db = make_desc(sb + SM_WO + beta * 16384, 65536, 1024);
    wgmma_fence();
#pragma unroll
    for (int j = 0; j < 8; j++) wgmma_m64n128k16_rs(acc2, z[j], db + j * 128);
    wgmma_commit();
}
__device__ __forceinline__ bool wg_any(bool p) {
    uint32_t r;
    asm volatile("{\n.reg .pred a, b;\nsetp.ne.u32 a, %1, 0;\nbarrier.cta.red.or.aligned.pred b, 1, 128, a;\nselp.u32 %0, 1, 0, b;\n}\n"
                 : "=r"(r) : "r"((uint32_t)p) : "memory");
    return r != 0;
}
template <int I>
__device__ __forceinline__ void z_repair(float (&acc2)[64], uint32_t sb, const uint8_t* src, int beta, int warp, int lane, uint32_t mine,
                                         uint32_t& rph) {
    if (!wg_any(mine != 0u)) return;
    uint32_t z[8][4];
    if (mine) {
        const uint32_t zo = sb + sm_zin(I) + warp * 4096;
        const uint32_t zs = sb + SM_ZFIX + warp * 4096;
        const uint32_t bar = sb + SM_BAR + 8 * (BAR_RETRY + warp);
        int spins = 0;
        do {
            __syncwarp();
            if (lane == 0) {
                mbar_expect_tx(bar, 4096);
                bulk_load(zs, src, 4096, bar);
            }
            mbar_wait(bar, rph);
            rph ^= 1;
#pragma unroll
            for (int j = 0; j < 8; j++) ldsm_x4_trans(z[j], zs + j * 512 + lane * 16);
        } while (!z_check(z) && ++spins < (1 << 16));
#pragma unroll
        for (int j = 0; j < 8; j++) {
            uint32_t o[4];
            ldsm_x4_trans(o, zo + j * 512 + lane * 16);
#pragma unroll
            for (int k = 0; k < 4; k++) z[j][k] &= __vcmpeq2(o[k], 0u);
        }
    } else {
#pragma unroll
        for (int j = 0; j < 8; j++)
#pragma unroll
            for (int k = 0; k < 4; k++) z[j][k] = 0u;
    }
    z_issue(acc2, z, sb, beta);
    wgmma_wait<0>();
}

template <int H>
__device__ __forceinline__ void store_half(const float (&a)[64], const float (&b)[32], uint32_t stg, const __nv_bfloat16* orow, int tok0, int lane) {
    const uint32_t st = stg + H * 2048 + (lane & 15) * 128;
    const int csel = lane >> 4, sw = lane & 7;
#pragma unroll
    for (int j2 = 0; j2 < 4; j2++) {
        const int j = 2 * j2, o = 32 * H + 4 * j;
        const uint32_t r0 = pack_bf16(a[o + 0] + b[4 * j + 0], a[o + 1] + b[4 * j + 1]);
        const uint32_t r1 = pack_bf16(a[o + 2] + b[4 * j + 2], a[o + 3] + b[4 * j + 3]);
        const uint32_t r2 = pack_bf16(a[o + 4] + b[4 * j + 4], a[o + 5] + b[4 * j + 5]);
        const uint32_t r3 = pack_bf16(a[o + 6] + b[4 * j + 6], a[o + 7] + b[4 * j + 7]);
        stsm_x4(st + (((j + csel) ^ sw) << 4), r0, r1, r2, r3);
    }
    __syncwarp();
#pragma unroll
    for (int i = 0; i < 4; i++) {
        const int r = 4 * i + (lane >> 3);
        uint32_t v0, v1, v2, v3;
        asm volatile("ld.shared.v4.b32 {%0, %1, %2, %3}, [%4];" : "=r"(v0), "=r"(v1), "=r"(v2), "=r"(v3)
                     : "r"(stg + H * 2048 + r * 128 + (((lane & 7) ^ (r & 7)) << 4)) : "memory");
        const int dt = (i & 1) * 16 + (i >> 1) * 2;
        asm volatile("{\n.reg .pred p;\nsetp.lt.s32 p, %5, %6;\n@p st.global.v4.b32 [%0], {%1, %2, %3, %4};\n}\n"
                     ::"l"(orow + dt * D_CH + H * 64), "r"(v0), "r"(v1), "r"(v2), "r"(v3), "r"(tok0), "r"(T_LEN - dt) : "memory");
    }
}

__global__ void __launch_bounds__(NTHREADS, 1)
wavenet_fused_kernel(const __grid_constant__ CUtensorMap mapX, const __grid_constant__ CUtensorMap mapW,
                     const __grid_constant__ CUtensorMap mapWo, __nv_bfloat16* __restrict__ out, const uint32_t zero) {
    extern __shared__ __align__(1024) uint8_t smem_raw[];
    const uint32_t sb = smem_u32(smem_raw);
    const uint32_t bars = sb + SM_BAR;
    const int warp = threadIdx.x >> 5;
    const int lane = threadIdx.x & 31;
    const int cg = blockIdx.x & 15;
    const int tt = blockIdx.x >> 4;
    const int batch = tt >> 2;
    const int t0 = (tt & 3) * NTOK;
    const int c4 = cg & 3, q = cg >> 2;

    if (threadIdx.x == 160) {
        prefetch_tmap(&mapW);
        prefetch_tmap(&mapX);
    }
    if (threadIdx.x == 128) {
        PROFG(0);
        const uint32_t xf = bars + 8 * BAR_XFULL;
        mbar_init(xf, 1);
        mbar_init(bars + 8 * BAR_WFULL, 1);
        asm volatile("fence.mbarrier_init.release.cluster;" ::: "memory");
        fence_proxy_async_smem();
        mbar_expect_tx(bars + 8 * BAR_WFULL, WBYTES);
        tma_load_3d(sb + SM_W, &mapW, bars + 8 * BAR_WFULL, cg * 32, 0, 0);
        mbar_expect_tx(xf, XBYTES);
#pragma unroll
        for (int j = 0; j < 3; j++) tma_load_3d(sb + SM_X + j * XBOX * 128, &mapX, xf, 0, t0 - 8 + j * XBOX, batch);
        for (int i = 1; i < WST; i++) mbar_init(bars + 8 * (BAR_WFULL + i), 1);
        asm volatile("fence.mbarrier_init.release.cluster;" ::: "memory");
        fence_proxy_async_smem();
#pragma unroll
        for (int i = 1; i < WST; i++) {
            mbar_expect_tx(bars + 8 * (BAR_WFULL + i), WBYTES);
            tma_load_3d(sb + SM_W + i * WBYTES, &mapW, bars + 8 * (BAR_WFULL + i), cg * 32, i * 512, 0);
        }
    } else if (threadIdx.x == 0) {
        for (int i = 0; i < WST; i++) mbar_init(bars + 8 * (BAR_WEMPTY + i), 4);
        mbar_init(bars + 8 * (BAR_XFULL + 1), 1);
        for (int i = 0; i < XST; i++) mbar_init(bars + 8 * (BAR_XEMPTY + i), 4);
        mbar_init(bars + 8 * BAR_WO, 1);
        mbar_init(bars + 8 * BAR_PAR, 1);
        for (int i = 0; i < 4; i++) {
            mbar_init(bars + 8 * (BAR_Z + i), 1);
            mbar_init(bars + 8 * (BAR_RETRY + i), 1);
        }
        asm volatile("fence.mbarrier_init.release.cluster;" ::: "memory");
    }
    __syncthreads();

    if (warp >= 4) {
        if (warp == 4) {
            if (lane == 0) {
                int ws = 0, wph = 0;
                for (int kc = 0; kc < 8; kc++) {
                    const int xs = kc & 1;
                    if (kc > 0) {
                        mbar_wait(bars + 8 * (BAR_XEMPTY + xs), ((kc >> 1) & 1) ^ 1);
                        const uint32_t xf = bars + 8 * (BAR_XFULL + xs);
                        mbar_expect_tx(xf, XBYTES);
                        const uint32_t xd = sb + SM_X + xs * XBYTES;
#pragma unroll
                        for (int j = 0; j < 3; j++) tma_load_3d(xd + j * XBOX * 128, &mapX, xf, kc * 64, t0 - 8 + j * XBOX, batch);
                    } else {
                        prefetch_tmap(&mapWo);
                    }
                    for (int tap = (kc == 0 ? WST : 0); tap < 5; tap++) {
                        mbar_wait(bars + 8 * (BAR_WEMPTY + ws), wph);
                        const uint32_t wf = bars + 8 * (BAR_WFULL + ws);
                        mbar_expect_tx(wf, WBYTES);
                        tma_load_3d(sb + SM_W + ws * WBYTES, &mapW, wf, cg * 32, tap * 512 + kc * 64, 0);
                        if (++ws == WST) { ws = 0; wph ^= 1; }
                        const int it = kc * 5 + tap - 10;
                        if (it >= 0 && it < 16) {
                            const uint32_t wob = bars + 8 * BAR_WO;
                            if (it == 0) mbar_expect_tx(wob, WO_BYTES);
                            tma_load_2d(sb + SM_WO + (it & 1) * 65536 + (it >> 1) * 8192, &mapWo, wob, c4 * 128 + (it & 1) * 64, (it >> 1) * 64);
                        }
                    }
                }
            }
            __syncwarp();
        } else if (warp == 5) {
            unsigned int par = 0;
            if (lane == 0) par = (atomicAdd(&g_ticket, 1u) >> 7) & 1u;
            par = __shfl_sync(0xffffffffu, par, 0);
            __nanosleep(1500);
            uint4* mine = &g_zx[par][tt * 4 * 4096 + q * 1024 + 2 * c4 * 32];
#pragma unroll 1
            for (int i = 0; i < 32; i++) {
                mine[(i >> 3) * 4096 + ((i >> 1) & 3) * 256 + (i & 1) * 32 + lane] = make_uint4(0u, 0u, 0u, 0u);
                __nanosleep(100);
            }
            __syncwarp();
            if (lane == 0) {
                asm volatile("st.shared.u32 [%0], %1;" ::"r"(sb + SM_PAR), "r"(par) : "memory");
                mbar_arrive(bars + 8 * BAR_PAR);
            }
            uint4* clr = &g_zx[par ^ 1][blockIdx.x * 1024];
#pragma unroll 1
            for (int i = 0; i < 32; i++) {
                clr[i * 32 + lane] = make_uint4(0u, 0u, 0u, 0u);
                __nanosleep(64);
            }
        }
        mbar_wait(bars + 8 * BAR_PAR, 0);
        uint32_t par;
        asm volatile("ld.shared.u32 %0, [%1];" : "=r"(par) : "r"(sb + SM_PAR) : "memory");
        const uint8_t* zsrc = reinterpret_cast<const uint8_t*>(&g_zx[par][(tt * 4 + q) * 4096]);
        fetch_slot(7 - warp, sb, zsrc, q, lane);
    } else {
        float acc[128];
#pragma unroll
        for (int i = 0; i < 128; i++) acc[i] = 0.f;
        uint32_t afr[2][4][4];
        const int lk = ((lane >> 4) << 3) + (lane & 7);
        const uint32_t a_lane_off = ((lane >> 3) & 1) * 4096 + lk * 64 + ((warp ^ ((lk >> 1) & 3)) << 4);
        int ws = 0, wph = 0;
        uint32_t par = 0;
        if (threadIdx.x == 0) PROF(1);
#pragma unroll 1
        for (int kc2 = 0; kc2 < 4; kc2++) {
#pragma unroll
            for (int u = 0; u < 10; u++) {
                const int xs = u / 5;
                const int tap = u % 5;
                if (u == 5 && kc2 == 3) break;
                if (tap == 0) mbar_wait(bars + 8 * (BAR_XFULL + xs), kc2 & 1);
                mbar_wait(bars + 8 * (BAR_WFULL + ws), wph);
                if (kc2 == 0 && u == 0 && threadIdx.x == 0) PROF(2);
                const uint32_t wa = sb + SM_W + ws * WBYTES + a_lane_off;
                load_w_frags(afr[u & 1], wa);
                __syncwarp();
                if (lane == 0) mbar_arrive(bars + 8 * (BAR_WEMPTY + ws));
                scale_w_frags(afr[u & 1]);
                if (++ws == WST) { ws = 0; wph ^= 1; }
                const uint64_t db = make_desc(sb + SM_X + xs * XBYTES + (8 - 2 * tap) * 128, 16, 1024);
                wgmma_fence();
#pragma unroll
                for (int kk = 0; kk < 4; kk++) {
                    wgmma_m64n128k16_rs_half<0>(acc, afr[u & 1][kk], db + kk * 2);
                    wgmma_m64n128k16_rs_half<64>(acc, afr[u & 1][kk], db + kk * 2 + 1024);
                }
                wgmma_commit();
                if (u == 2 && kc2 == 3) {
                    mbar_wait(bars + 8 * BAR_PAR, 0);
                    asm volatile("ld.shared.u32 %0, [%1];" : "=r"(par) : "r"(sb + SM_PAR) : "memory");
                    mbar_wait(bars + 8 * BAR_WO, 0);
                }
                wgmma_wait<1>();
                if (tap == 0 && (u > 0 || kc2 > 0)) {
                    if (lane == 0) mbar_arrive(bars + 8 * (BAR_XEMPTY + (xs ^ 1)));
                }
            }
        }
        uint8_t* zx = reinterpret_cast<uint8_t*>(&g_zx[par][tt * 4 * 4096]);
        uint8_t* zdst = zx + q * 16384 + (2 * c4 + (warp >> 1)) * 512 + (warp & 1) * 256 +
                        ((lane >> 1) & 1) * 4096 + (lane & 1) * 128 + (lane >> 2) * 16;
        switch (q) {
            case 0: tail_gemm1<0>(acc, afr, sb, ws, wph, a_lane_off, zdst, lane, zero); break;
            case 1: tail_gemm1<1>(acc, afr, sb, ws, wph, a_lane_off, zdst, lane, zero); break;
            case 2: tail_gemm1<2>(acc, afr, sb, ws, wph, a_lane_off, zdst, lane, zero); break;
            default: tail_gemm1<3>(acc, afr, sb, ws, wph, a_lane_off, zdst, lane, zero); break;
        }
        if (threadIdx.x == 0) PROF(4);

        float acc2[64], acc3a[32], acc3b[32];
#pragma unroll
        for (int i = 0; i < 64; i++) acc2[i] = 0.f;
        const uint32_t stg = sb + SM_OSTG + warp * 4096;
        const int tok0 = t0 + q * 64 + (warp >> 1) * 32 + (warp & 1) * 4 + (lane >> 4) * 8 + ((lane >> 3) & 1);
        const __nv_bfloat16* orow = out + ((size_t)batch * T_LEN + tok0) * D_CH + c4 * 128 + (lane & 7) * 8;
        uint32_t bad;
        {
            uint32_t za[3][8][4];
            z_load<0>(za[0], sb, warp, lane);
            if (threadIdx.x == 0) PROF(12);
            z_issue(acc2, za[0], sb, q ^ 0);
            z_load<1>(za[1], sb, warp, lane);
            bad = z_check(za[0]) ? 0u : 1u;
            if (threadIdx.x == 0) PROF(13);
            z_issue(acc2, za[1], sb, q ^ 1);
            z_load<2>(za[2], sb, warp, lane);
            bad |= z_check(za[1]) ? 0u : 2u;
            if (threadIdx.x == 0) PROF(14);
            z_issue(acc2, za[2], sb, q ^ 2);
            wgmma_wait<2>();
            z_load<3>(za[0], sb, warp, lane);
            bad |= z_check(za[2]) ? 0u : 4u;
            if (threadIdx.x == 0) PROF(15);
#pragma unroll
            for (int j = 0; j < 8; j++) asm volatile("" : "+r"(za[0][j][0]), "+r"(za[0][j][1]), "+r"(za[0][j][2]), "+r"(za[0][j][3]) :: "memory");
            const uint64_t db = make_desc(sb + SM_WO + (q ^ 3) * 16384, 65536, 1024);
            wgmma_fence();
#pragma unroll
            for (int j = 0; j < 8; j++) wgmma_m64n64k16_rs(acc3a, za[0][j], db + j * 128, j);
            wgmma_commit();
#pragma unroll
            for (int j = 0; j < 8; j++) wgmma_m64n64k16_rs(acc3b, za[0][j], db + j * 128 + 4096, j);
            wgmma_commit();
            wgmma_wait<1>();
            fence_regs(acc2);
            fence_regs(acc3a);
            if (threadIdx.x == 0) PROF(10);
            store_half<0>(acc2, acc3a, stg, orow, tok0, lane);
            sched_fence<7>(zero);
            bad |= z_check(za[0]) ? 0u : 8u;
        }
        wgmma_wait<0>();
        fence_regs(acc3b);
        store_half<1>(acc2, acc3b, stg, orow, tok0, lane);
        if (__builtin_expect(wg_any(bad != 0u), 0)) {
            const uint8_t* zsrc = zx + q * 65536 + warp * 4096;
            uint32_t rph = 0;
            z_repair<0>(acc2, sb, zsrc + (q ^ 0) * 16384, q ^ 0, warp, lane, bad & 1u, rph);
            z_repair<1>(acc2, sb, zsrc + (q ^ 1) * 16384, q ^ 1, warp, lane, bad & 2u, rph);
            z_repair<2>(acc2, sb, zsrc + (q ^ 2) * 16384, q ^ 2, warp, lane, bad & 4u, rph);
            z_repair<3>(acc2, sb, zsrc + (q ^ 3) * 16384, q ^ 3, warp, lane, bad & 8u, rph);
            fence_regs(acc2);
            __syncwarp();
            store_half<0>(acc2, acc3a, stg, orow, tok0, lane);
            store_half<1>(acc2, acc3b, stg, orow, tok0, lane);
        }
        if (threadIdx.x == 0) PROFG(11);
    }
}

typedef CUresult (*EncodeFn)(CUtensorMap*, CUtensorMapDataType, cuuint32_t, void*, const cuuint64_t*, const cuuint64_t*,
                             const cuuint32_t*, const cuuint32_t*, CUtensorMapInterleave, CUtensorMapSwizzle,
                             CUtensorMapL2promotion, CUtensorMapFloatOOBfill);

void encode(EncodeFn fn, CUtensorMap* m, const void* ptr, int rank, const cuuint64_t* dims, const cuuint64_t* strides,
            const cuuint32_t* box, CUtensorMapSwizzle sw) {
    cuuint32_t es[3] = {1, 1, 1};
    fn(m, CU_TENSOR_MAP_DATA_TYPE_BFLOAT16, rank, const_cast<void*>(ptr), dims, strides, box, es,
       CU_TENSOR_MAP_INTERLEAVE_NONE, sw, CU_TENSOR_MAP_L2_PROMOTION_L2_128B, CU_TENSOR_MAP_FLOAT_OOB_FILL_NONE);
}

}

extern "C" void kernel_launch(void* const* d_in, const int* in_sizes, int n_in, void* d_out, int out_size) {
    (void)in_sizes; (void)n_in; (void)out_size;
    static EncodeFn enc = nullptr;
    if (!enc) {
        void* fn = nullptr;
        cudaDriverEntryPointQueryResult qr;
        cudaGetDriverEntryPoint("cuTensorMapEncodeTiled", &fn, cudaEnableDefault, &qr);
        enc = (EncodeFn)fn;
        cudaFuncSetAttribute(wavenet_fused_kernel, cudaFuncAttributeMaxDynamicSharedMemorySize, SM_TOTAL);
    }
    CUtensorMap mX, mW, mWo;
    {
        cuuint64_t dims[3] = {512, (cuuint64_t)T_LEN, 2}, str[2] = {1024, (cuuint64_t)T_LEN * 1024};
        cuuint32_t box[3] = {64, XBOX, 1};
        encode(enc, &mX, d_in[0], 3, dims, str, box, CU_TENSOR_MAP_SWIZZLE_128B);
    }
    {
        cuuint64_t dims[3] = {512, 2560, 2}, str[2] = {2048, 1024};
        cuuint32_t box[3] = {32, 64, 2};
        encode(enc, &mW, d_in[1], 3, dims, str, box, CU_TENSOR_MAP_SWIZZLE_64B);
    }
    {
        cuuint64_t dims[2] = {512, 512}, str[1] = {1024};
        cuuint32_t box[2] = {64, 64};
        encode(enc, &mWo, d_in[2], 2, dims, str, box, CU_TENSOR_MAP_SWIZZLE_128B);
    }
    wavenet_fused_kernel<<<128, NTHREADS, SM_TOTAL>>>(mX, mW, mWo, (__nv_bfloat16*)d_out, 0u);
}
```

```cpp
#include <cuda_runtime.h>
#include <cuda_bf16.h>
#include <cuda.h>
#include <stdint.h>

namespace {

constexpr int T_LEN   = 1000;
constexpr int D_CH    = 512;
constexpr int NTOK    = 256;
constexpr int XROWS   = NTOK + 8;
constexpr int XBYTES  = XROWS * 128;
constexpr int XBOX    = 88;
constexpr int XST     = 2;
constexpr int WST     = 4;
constexpr int WBYTES  = 8192;
constexpr int WO_BYTES = 131072;

constexpr int SM_WO   = 0;
constexpr int SM_X    = SM_WO + WO_BYTES;
constexpr int SM_W    = SM_X + XST * XBYTES;
constexpr int SM_BAR  = SM_W + WST * WBYTES;
constexpr int SM_TOTAL = SM_BAR + 256;
__host__ __device__ constexpr int sm_zin(int i) { return SM_X + (i >> 1) * XBYTES + (i & 1) * 16384; }
constexpr int SM_OSTG  = SM_W;
constexpr int SM_ZFIX  = SM_W + 16384;

constexpr int BAR_WFULL  = 0;
constexpr int BAR_WEMPTY = BAR_WFULL + WST;
constexpr int BAR_XFULL  = BAR_WEMPTY + WST;
constexpr int BAR_XEMPTY = BAR_XFULL + XST;
constexpr int BAR_WO     = BAR_XEMPTY + XST;
constexpr int BAR_PAR    = BAR_WO + 1;
constexpr int BAR_Z      = BAR_PAR + 1;
constexpr int BAR_RETRY  = BAR_Z + 4;

constexpr int SM_PAR   = SM_BAR + 240;
constexpr int NTHREADS = 256;
constexpr int MS = 2;
constexpr int AS = 2;
constexpr int HS = 4;
constexpr int HS3 = 4;
#define ZDELAY0 650
#define ZDELAY1 600
#define ZDELAY2 650
#define ZDELAY3 600

__device__ uint4 g_zx[2][8 * 4 * 4096];
__device__ unsigned int g_ticket;

#define PROF(i)
#define PROFG(i)

__device__ __forceinline__ uint32_t smem_u32(const void* p) { return (uint32_t)__cvta_generic_to_shared(p); }

__device__ __forceinline__ void mbar_init(uint32_t bar, uint32_t cnt) {
    asm volatile("mbarrier.init.shared::cta.b64 [%0], %1;" ::"r"(bar), "r"(cnt));
}
__device__ __forceinline__ void mbar_expect_tx(uint32_t bar, uint32_t bytes) {
    asm volatile("mbarrier.arrive.expect_tx.shared::cta.b64 _, [%0], %1;" ::"r"(bar), "r"(bytes) : "memory");
}
__device__ __forceinline__ void mbar_arrive(uint32_t bar) {
    asm volatile("mbarrier.arrive.shared::cta.b64 _, [%0];" ::"r"(bar) : "memory");
}
__device__ __forceinline__ void mbar_wait(uint32_t bar, uint32_t parity) {
    asm volatile(
        "{\n"
        ".reg .pred p;\n"
        "WAIT_LOOP:\n"
        "mbarrier.try_wait.parity.shared::cta.b64 p, [%0], %1;\n"
        "@p bra WAIT_DONE;\n"
        "bra WAIT_LOOP;\n"
        "WAIT_DONE:\n"
        "}\n" ::"r"(bar), "r"(parity) : "memory");
}
__device__ __forceinline__ void tma_load_3d(uint32_t dst, const CUtensorMap* m, uint32_t bar, int c0, int c1, int c2) {
    asm volatile("cp.async.bulk.tensor.3d.shared::cluster.global.mbarrier::complete_tx::bytes [%0], [%1, {%3, %4, %5}], [%2];"
                 ::"r"(dst), "l"(m), "r"(bar), "r"(c0), "r"(c1), "r"(c2) : "memory");
}
__device__ __forceinline__ void tma_load_2d(uint32_t dst, const CUtensorMap* m, uint32_t bar, int c0, int c1) {
    asm volatile("cp.async.bulk.tensor.2d.shared::cluster.global.mbarrier::complete_tx::bytes [%0], [%1, {%3, %4}], [%2];"
                 ::"r"(dst), "l"(m), "r"(bar), "r"(c0), "r"(c1) : "memory");
}
__device__ __forceinline__ void fence_proxy_async_smem() { asm volatile("fence.proxy.async.shared::cta;" ::: "memory"); }
__device__ __forceinline__ void prefetch_tmap(const CUtensorMap* m) {
    asm volatile("prefetch.tensormap [%0];" ::"l"(m) : "memory");
}
__device__ __forceinline__ void wgmma_fence() { asm volatile("wgmma.fence.sync.aligned;" ::: "memory"); }
__device__ __forceinline__ void wgmma_commit() { asm volatile("wgmma.commit_group.sync.aligned;" ::: "memory"); }
template <int N> __device__ __forceinline__ void wgmma_wait() {
    asm volatile("wgmma.wait_group.sync.aligned %0;" ::"n"(N) : "memory");
}
template <int N> __device__ __forceinline__ void fence_regs(float (&d)[N]) {
#pragma unroll
    for (int i = 0; i < N; i++) asm volatile("" : "+f"(d[i]) :: "memory");
}
__device__ __forceinline__ void ldsm_x4_trans(uint32_t (&r)[4], uint32_t addr) {
    asm volatile("ldmatrix.sync.aligned.m8n8.x4.trans.shared.b16 {%0, %1, %2, %3}, [%4];"
                 : "=r"(r[0]), "=r"(r[1]), "=r"(r[2]), "=r"(r[3]) : "r"(addr) : "memory");
}
__device__ __forceinline__ void stsm_x4(uint32_t addr, uint32_t a, uint32_t b, uint32_t c, uint32_t d) {
    asm volatile("stmatrix.sync.aligned.m8n8.x4.shared.b16 [%0], {%1, %2, %3, %4};"
                 ::"r"(addr), "r"(a), "r"(b), "r"(c), "r"(d) : "memory");
}
__device__ __forceinline__ void st_relaxed_v4(void* p, uint32_t a, uint32_t b, uint32_t c, uint32_t d) {
    asm volatile("st.relaxed.gpu.global.v4.b32 [%0], {%1, %2, %3, %4};" ::"l"(p), "r"(a), "r"(b), "r"(c), "r"(d) : "memory");
}
__device__ __forceinline__ void bulk_load(uint32_t dst, const void* src, uint32_t bytes, uint32_t bar) {
    asm volatile("cp.async.bulk.shared::cluster.global.mbarrier::complete_tx::bytes [%0], [%1], %2, [%3];"
                 ::"r"(dst), "l"(src), "r"(bytes), "r"(bar) : "memory");
}
__device__ __forceinline__ uint32_t clock_now() {
    uint32_t t;
    asm volatile("mov.u32 %0, %%clock;" : "=r"(t) :: "memory");
    return t;
}
template <int BIT>
__device__ __forceinline__ void sched_fence(uint32_t zero) {
    asm volatile("{\n.reg .pred p;\n.reg .b32 t;\nand.b32 t, %0, %1;\nsetp.eq.u32 p, t, 0;\n@p bra SF_DONE;\ntrap;\nSF_DONE:\n}\n"
                 ::"r"(zero), "n"(1u << BIT) : "memory");
}
__device__ __forceinline__ float tanh_fast(float x) {
    float y;
    asm volatile("tanh.approx.f32 %0, %1;" : "=f"(y) : "f"(x));
    return y;
}
__device__ __forceinline__ void load_w_frags(uint32_t (&f)[4][4], uint32_t wa) {
#pragma unroll
    for (int kk = 0; kk < 4; kk++) ldsm_x4_trans(f[kk], wa + kk * 1024);
}
__device__ __forceinline__ void scale_w_frag(uint32_t (&f)[4]) {
    asm volatile("mul.rn.bf16x2 %0, %0, %1;" : "+r"(f[1]) : "r"(0x3F003F00u));
    asm volatile("mul.rn.bf16x2 %0, %0, %1;" : "+r"(f[3]) : "r"(0x3F003F00u));
}
__device__ __forceinline__ uint32_t pack_bf16(float lo, float hi) {
    uint32_t r;
    asm("cvt.rn.bf16x2.f32 %0, %1, %2;" : "=r"(r) : "f"(hi), "f"(lo));
    return r;
}
__device__ __forceinline__ uint64_t make_desc(uint32_t addr, uint32_t lbo_bytes, uint32_t sbo_bytes) {
    return (uint64_t)((addr & 0x3FFFF) >> 4) | ((uint64_t)(lbo_bytes >> 4) << 16) | ((uint64_t)(sbo_bytes >> 4) << 32) |
           ((uint64_t)1 << 62);
}

#define R8(d, o) "+f"(d[o + 0]), "+f"(d[o + 1]), "+f"(d[o + 2]), "+f"(d[o + 3]), "+f"(d[o + 4]), "+f"(d[o + 5]), "+f"(d[o + 6]), "+f"(d[o + 7])

__device__ __forceinline__ void wgmma_m64n128k16_rs(float (&d)[64], const uint32_t (&a)[4], uint64_t descB) {
    asm volatile(
        "wgmma.mma_async.sync.aligned.m64n128k16.f32.bf16.bf16 "
        "{%0, %1, %2, %3, %4, %5, %6, %7, %8, %9, %10, %11, %12, %13, %14, %15, "
        "%16, %17, %18, %19, %20, %21, %22, %23, %24, %25, %26, %27, %28, %29, %30, %31, "
        "%32, %33, %34, %35, %36, %37, %38, %39, %40, %41, %42, %43, %44, %45, %46, %47, "
        "%48, %49, %50, %51, %52, %53, %54, %55, %56, %57, %58, %59, %60, %61, %62, %63}, "
        "{%64, %65, %66, %67}, %68, 1, -1, 1, 1;\n"
        : R8(d, 0), R8(d, 8), R8(d, 16), R8(d, 24), R8(d, 32), R8(d, 40), R8(d, 48), R8(d, 56)
        : "r"(a[0]), "r"(a[1]), "r"(a[2]), "r"(a[3]), "l"(descB));
}

__device__ __forceinline__ void wgmma_m64n64k16_rs(float (&d)[32], const uint32_t (&a)[4], uint64_t descB, int scale_d) {
    asm volatile(
        "{\n"
        ".reg .pred p;\n"
        "setp.ne.b32 p, %37, 0;\n"
        "wgmma.mma_async.sync.aligned.m64n64k16.f32.bf16.bf16 "
        "{%0, %1, %2, %3, %4, %5, %6, %7, %8, %9, %10, %11, %12, %13, %14, %15, "
        "%16, %17, %18, %19, %20, %21, %22, %23, %24, %25, %26, %27, %28, %29, %30, %31}, "
        "{%32, %33, %34, %35}, %36, p, -1, 1, 1;\n"
        "}\n"
        : R8(d, 0), R8(d, 8), R8(d, 16), R8(d, 24)
        : "r"(a[0]), "r"(a[1]), "r"(a[2]), "r"(a[3]), "l"(descB), "r"(scale_d));
}

template <int OFF>
__device__ __forceinline__ void wgmma_m64n128k16_rs_half(float (&d)[128], const uint32_t (&a)[4], uint64_t descB) {
    asm volatile(
        "wgmma.mma_async.sync.aligned.m64n128k16.f32.bf16.bf16 "
        "{%0, %1, %2, %3, %4, %5, %6, %7, %8, %9, %10, %11, %12, %13, %14, %15, "
        "%16, %17, %18, %19, %20, %21, %22, %23, %24, %25, %26, %27, %28, %29, %30, %31, "
        "%32, %33, %34, %35, %36, %37, %38, %39, %40, %41, %42, %43, %44, %45, %46, %47, "
        "%48, %49, %50, %51, %52, %53, %54, %55, %56, %57, %58, %59, %60, %61, %62, %63}, "
        "{%64, %65, %66, %67}, %68, 1, 1, 1, 0;\n"
        : R8(d, OFF + 0), R8(d, OFF + 8), R8(d, OFF + 16), R8(d, OFF + 24), R8(d, OFF + 32), R8(d, OFF + 40), R8(d, OFF + 48), R8(d, OFF + 56)
        : "r"(a[0]), "r"(a[1]), "r"(a[2]), "r"(a[3]), "l"(descB));
}
template <int OFF> __device__ __forceinline__ void fence_half(float (&d)[128]) {
#pragma unroll
    for (int i = 0; i < 64; i++) asm volatile("" : "+f"(d[OFF + i]) :: "memory");
}

template <int Q0, int N> struct GateGroup { static constexpr int J = 2 * (Q0 ^ (N >> 1)) + (N & 1); };

template <int Q0, int N>
__device__ __forceinline__ void gate_mufu(float (&acc)[128]) {
    constexpr int J = GateGroup<Q0, N>::J;
#pragma unroll
    for (int i = 0; i < 16; i++) acc[16 * J + i] = tanh_fast(acc[16 * J + i]);
}
template <int Q0, int N>
__device__ __forceinline__ void gate_finish(float (&acc)[128], uint8_t* zdst) {
    constexpr int J = GateGroup<Q0, N>::J;
    uint32_t zp[4];
#pragma unroll
    for (int i = 0; i < 4; i++) {
        const int r = 16 * J + 4 * i;
        zp[i] = __vmaxu2(pack_bf16(acc[r] * fmaf(acc[r + 2], -0.5f, -0.5f), acc[r + 1] * fmaf(acc[r + 3], -0.5f, -0.5f)), 0x00010001u);
    }
    st_relaxed_v4(zdst + (J >> 1) * 65536 + (J & 1) * 8192, zp[0], zp[1], zp[2], zp[3]);
    if (N & 1) asm volatile("bar.arrive %0, 160;" ::"n"(2 + (N >> 1)) : "memory");
}

template <int Q0>
__device__ __forceinline__ void tail_gemm1(float (&acc)[128], uint32_t (&afr)[2][4][4], uint32_t sb, int ws, int wph, uint32_t a_lane_off,
                                           uint8_t* zdst, int lane, uint32_t zero) {
    constexpr int OA = (Q0 >> 1) * 64;
    constexpr int OB = 64 - OA;
    const uint32_t bars = sb + SM_BAR;
    uint32_t fa[4][4], fb[4][4], fc[4][4];
    const int ws0 = ws;
    auto wtile = [&](int tap) { return sb + SM_W + ((ws0 + tap) & (WST - 1)) * WBYTES + a_lane_off; };
    auto wwait = [&](int tap) {
        const int st = ws0 + tap;
        mbar_wait(bars + 8 * (BAR_WFULL + (st & (WST - 1))), wph ^ ((st >> 2) & 1));
    };
    auto load = [&](uint32_t (&f)[4][4], int tap) { load_w_frags(f, wtile(tap)); };
    auto issueA = [&](uint32_t (&f)[4][4], int tap) {
        const uint64_t db = make_desc(sb + SM_X + XBYTES + (8 - 2 * tap) * 128 + OA * 256, 16, 1024);
#pragma unroll
        for (int h = 0; h < AS; h++) {
#pragma unroll
            for (int kk = h * (4 / AS); kk < (h + 1) * (4 / AS); kk++) scale_w_frag(f[kk]);
            wgmma_fence();
#pragma unroll
            for (int kk = h * (4 / AS); kk < (h + 1) * (4 / AS); kk++) wgmma_m64n128k16_rs_half<OA>(acc, f[kk], db + kk * 2);
            wgmma_commit();
        }
    };
    auto issueB = [&](uint32_t (&f)[4][4], int tap) {
        const uint64_t db = make_desc(sb + SM_X + XBYTES + (8 - 2 * tap) * 128 + OB * 256, 16, 1024);
        wgmma_fence();
#pragma unroll
        for (int kk = 0; kk < 4; kk++) wgmma_m64n128k16_rs_half<OB>(acc, f[kk], db + kk * 2);
        wgmma_commit();
    };
    mbar_wait(bars + 8 * (BAR_XFULL + 1), 1);
    wwait(0); load(fa, 0);
    __syncwarp();
    if (lane == 0) mbar_arrive(bars + 8 * (BAR_WEMPTY + ws0));
    wwait(1); load(fb, 1);
    wwait(2); load(fc, 2);
    issueA(fa, 0); wgmma_wait<AS>();
    wwait(3); load(afr[0], 3);
    issueA(fb, 1);
    issueA(fc, 2);
    wwait(4); load(afr[1], 4);
    issueA(afr[0], 3);
    issueA(afr[1], 4);
    if (threadIdx.x == 0) PROF(24);
    issueB(fa, 0);
    issueB(fb, 1);
    wgmma_wait<2>();
    fence_half<OA>(acc);
    sched_fence<0>(zero);
    gate_mufu<Q0, 0>(acc); gate_mufu<Q0, 1>(acc);
    gate_finish<Q0, 0>(acc, zdst); gate_finish<Q0, 1>(acc, zdst);
    sched_fence<1>(zero);
    issueB(fc, 2);
    issueB(afr[0], 3);
    sched_fence<2>(zero);
    gate_mufu<Q0, 2>(acc); gate_mufu<Q0, 3>(acc);
    sched_fence<3>(zero);
    issueB(afr[1], 4);
    sched_fence<4>(zero);
    gate_finish<Q0, 2>(acc, zdst); gate_finish<Q0, 3>(acc, zdst);
    wgmma_wait<0>();
    fence_half<OB>(acc);
    if (threadIdx.x == 0) PROF(3);
    gate_mufu<Q0, 4>(acc);
    gate_mufu<Q0, 5>(acc);
    gate_finish<Q0, 4>(acc, zdst);
    gate_finish<Q0, 5>(acc, zdst);
    sched_fence<5>(zero);
    gate_mufu<Q0, 6>(acc);
    gate_mufu<Q0, 7>(acc);
    gate_finish<Q0, 6>(acc, zdst);
    gate_finish<Q0, 7>(acc, zdst);
}

__device__ __forceinline__ void fetch_slot(int i, uint32_t sb, const uint8_t* zsrc, int q, int lane) {
    const uint32_t bars = sb + SM_BAR;
    asm volatile("bar.sync %0, 160;" ::"r"(2 + i) : "memory");
    if (lane == 0) {
        uint32_t t;
        asm volatile("mov.u32 %0, %%clock;" : "=r"(t) : "r"(lane) : "memory");
        const uint32_t delay = (i == 0) ? ZDELAY0 : (i == 1) ? ZDELAY1 : (i == 2) ? ZDELAY2 : ZDELAY3;
        while (clock_now() - t < delay) {}
        mbar_expect_tx(bars + 8 * (BAR_Z + i), 16384);
        bulk_load(sb + sm_zin(i), zsrc + (q ^ i) * 16384, 16384, bars + 8 * (BAR_Z + i));
        PROF(26 + i);
    }
    __syncwarp();
}

template <int I>
__device__ __forceinline__ void z_load(uint32_t (&z)[8][4], uint32_t sb, int warp, int lane) {
    mbar_wait(sb + SM_BAR + 8 * (BAR_Z + I), 0);
#pragma unroll
    for (int j = 0; j < 8; j++) ldsm_x4_trans(z[j], sb + sm_zin(I) + warp * 4096 + j * 512 + lane * 16);
}
__device__ __forceinline__ bool z_check(const uint32_t (&z)[8][4]) {
    uint32_t m0 = 0xFFFFFFFFu, m1 = 0xFFFFFFFFu;
#pragma unroll
    for (int j = 0; j < 8; j++) {
        m0 = __vimin3_u16x2(m0, z[j][0], z[j][1]);
        m1 = __vimin3_u16x2(m1, z[j][2], z[j][3]);
    }
    m0 = __vminu2(m0, m1);
    return __all_sync(0xffffffffu, ((m0 & 0xFFFFu) != 0u) && ((m0 >> 16) != 0u));
}
__device__ __forceinline__ void z_issue(float (&acc2)[64], uint32_t (&z)[8][4], uint32_t sb, int beta) {
    const uint64_t db = make_desc(sb + SM_WO + beta * 16384, 65536, 1024);
#pragma unroll
    for (int h = 0; h < HS; h++) {
#pragma unroll
        for (int j = h * (8 / HS); j < (h + 1) * (8 / HS); j++)
            asm volatile("" : "+r"(z[j][0]), "+r"(z[j][1]), "+r"(z[j][2]), "+r"(z[j][3]) :: "memory");
        wgmma_fence();
#pragma unroll
        for (int j = h * (8 / HS); j < (h + 1) * (8 / HS); j++) wgmma_m64n128k16_rs(acc2, z[j], db + j * 128);
        wgmma_commit();
    }
}
__device__ __forceinline__ bool wg_any(bool p) {
    uint32_t r;
    asm volatile("{\n.reg .pred a, b;\nsetp.ne.u32 a, %1, 0;\nbarrier.cta.red.or.aligned.pred b, 1, 128, a;\nselp.u32 %0, 1, 0, b;\n}\n"
                 : "=r"(r) : "r"((uint32_t)p) : "memory");
    return r != 0;
}
template <int I>
__device__ __forceinline__ void z_repair(float (&acc2)[64], uint32_t sb, const uint8_t* src, int beta, int warp, int lane, uint32_t mine,
                                         uint32_t& rph) {
    if (!wg_any(mine != 0u)) return;
    uint32_t z[8][4];
    if (mine) {
        const uint32_t zo = sb + sm_zin(I) + warp * 4096;
        const uint32_t zs = sb + SM_ZFIX + warp * 4096;
        const uint32_t bar = sb + SM_BAR + 8 * (BAR_RETRY + warp);
        int spins = 0;
        do {
            __syncwarp();
            if (lane == 0) {
                mbar_expect_tx(bar, 4096);
                bulk_load(zs, src, 4096, bar);
            }
            mbar_wait(bar, rph);
            rph ^= 1;
#pragma unroll
            for (int j = 0; j < 8; j++) ldsm_x4_trans(z[j], zs + j * 512 + lane * 16);
        } while (!z_check(z) && ++spins < (1 << 16));
#pragma unroll
        for (int j = 0; j < 8; j++) {
            uint32_t o[4];
            ldsm_x4_trans(o, zo + j * 512 + lane * 16);
#pragma unroll
            for (int k = 0; k < 4; k++) z[j][k] &= __vcmpeq2(o[k], 0u);
        }
    } else {
#pragma unroll
        for (int j = 0; j < 8; j++)
#pragma unroll
            for (int k = 0; k < 4; k++) z[j][k] = 0u;
    }
    z_issue(acc2, z, sb, beta);
    wgmma_wait<0>();
}

template <int H>
__device__ __forceinline__ void store_half(const float (&a)[64], const float (&b)[32], uint32_t stg, const __nv_bfloat16* orow, int tok0, int lane) {
    const uint32_t st = stg + H * 2048 + (lane & 15) * 128;
    const int csel = lane >> 4, sw = lane & 7;
#pragma unroll
    for (int j2 = 0; j2 < 4; j2++) {
        const int j = 2 * j2, o = 32 * H + 4 * j;
        const uint32_t r0 = pack_bf16(a[o + 0] + b[4 * j + 0], a[o + 1] + b[4 * j + 1]);
        const uint32_t r1 = pack_bf16(a[o + 2] + b[4 * j + 2], a[o + 3] + b[4 * j + 3]);
        const uint32_t r2 = pack_bf16(a[o + 4] + b[4 * j + 4], a[o + 5] + b[4 * j + 5]);
        const uint32_t r3 = pack_bf16(a[o + 6] + b[4 * j + 6], a[o + 7] + b[4 * j + 7]);
        stsm_x4(st + (((j + csel) ^ sw) << 4), r0, r1, r2, r3);
    }
    __syncwarp();
#pragma unroll
    for (int i = 0; i < 4; i++) {
        const int r = 4 * i + (lane >> 3);
        uint32_t v0, v1, v2, v3;
        asm volatile("ld.shared.v4.b32 {%0, %1, %2, %3}, [%4];" : "=r"(v0), "=r"(v1), "=r"(v2), "=r"(v3)
                     : "r"(stg + H * 2048 + r * 128 + (((lane & 7) ^ (r & 7)) << 4)) : "memory");
        const int dt = (i & 1) * 16 + (i >> 1) * 2;
        asm volatile("{\n.reg .pred p;\nsetp.lt.s32 p, %5, %6;\n@p st.global.v4.b32 [%0], {%1, %2, %3, %4};\n}\n"
                     ::"l"(orow + dt * D_CH + H * 64), "r"(v0), "r"(v1), "r"(v2), "r"(v3), "r"(tok0), "r"(T_LEN - dt) : "memory");
    }
}

__global__ void __launch_bounds__(NTHREADS, 1)
wavenet_fused_kernel(const __grid_constant__ CUtensorMap mapX, const __grid_constant__ CUtensorMap mapW,
                     const __grid_constant__ CUtensorMap mapWo, __nv_bfloat16* __restrict__ out, const uint32_t zero) {
    extern __shared__ __align__(1024) uint8_t smem_raw[];
    const uint32_t sb = smem_u32(smem_raw);
    const uint32_t bars = sb + SM_BAR;
    const int warp = threadIdx.x >> 5;
    const int lane = threadIdx.x & 31;
    const int cg = blockIdx.x & 15;
    const int tt = blockIdx.x >> 4;
    const int batch = tt >> 2;
    const int t0 = (tt & 3) * NTOK;
    const int c4 = cg & 3, q = cg >> 2;

    if (threadIdx.x == 160) {
        prefetch_tmap(&mapW);
        prefetch_tmap(&mapX);
    }
    if (threadIdx.x == 128) {
        PROFG(0);
        const uint32_t xf = bars + 8 * BAR_XFULL;
        mbar_init(xf, 1);
        mbar_init(bars + 8 * BAR_WFULL, 1);
        asm volatile("fence.mbarrier_init.release.cluster;" ::: "memory");
        fence_proxy_async_smem();
        mbar_expect_tx(bars + 8 * BAR_WFULL, WBYTES);
        tma_load_3d(sb + SM_W, &mapW, bars + 8 * BAR_WFULL, cg * 32, 0, 0);
        mbar_expect_tx(xf, XBYTES);
#pragma unroll
        for (int j = 0; j < 3; j++) tma_load_3d(sb + SM_X + j * XBOX * 128, &mapX, xf, 0, t0 - 8 + j * XBOX, batch);
        for (int i = 1; i < WST; i++) mbar_init(bars + 8 * (BAR_WFULL + i), 1);
        asm volatile("fence.mbarrier_init.release.cluster;" ::: "memory");
        fence_proxy_async_smem();
#pragma unroll
        for (int i = 1; i < WST; i++) {
            mbar_expect_tx(bars + 8 * (BAR_WFULL + i), WBYTES);
            tma_load_3d(sb + SM_W + i * WBYTES, &mapW, bars + 8 * (BAR_WFULL + i), cg * 32, i * 512, 0);
        }
    } else if (threadIdx.x == 0) {
        for (int i = 0; i < WST; i++) mbar_init(bars + 8 * (BAR_WEMPTY + i), 4);
        mbar_init(bars + 8 * (BAR_XFULL + 1), 1);
        for (int i = 0; i < XST; i++) mbar_init(bars + 8 * (BAR_XEMPTY + i), 4);
        mbar_init(bars + 8 * BAR_WO, 1);
        mbar_init(bars + 8 * BAR_PAR, 1);
        for (int i = 0; i < 4; i++) {
            mbar_init(bars + 8 * (BAR_Z + i), 1);
            mbar_init(bars + 8 * (BAR_RETRY + i), 1);
        }
        asm volatile("fence.mbarrier_init.release.cluster;" ::: "memory");
    }
    __syncthreads();

    if (warp >= 4) {
        if (warp == 4) {
            if (lane == 0) {
                int ws = 0, wph = 0;
                for (int kc = 0; kc < 8; kc++) {
                    const int xs = kc & 1;
                    if (kc > 0) {
                        mbar_wait(bars + 8 * (BAR_XEMPTY + xs), ((kc >> 1) & 1) ^ 1);
                        const uint32_t xf = bars + 8 * (BAR_XFULL + xs);
                        mbar_expect_tx(xf, XBYTES);
                        const uint32_t xd = sb + SM_X + xs * XBYTES;
#pragma unroll
                        for (int j = 0; j < 3; j++) tma_load_3d(xd + j * XBOX * 128, &mapX, xf, kc * 64, t0 - 8 + j * XBOX, batch);
                    } else {
                        prefetch_tmap(&mapWo);
                    }
                    for (int tap = (kc == 0 ? WST : 0); tap < 5; tap++) {
                        mbar_wait(bars + 8 * (BAR_WEMPTY + ws), wph);
                        const uint32_t wf = bars + 8 * (BAR_WFULL + ws);
                        mbar_expect_tx(wf, WBYTES);
                        tma_load_3d(sb + SM_W + ws * WBYTES, &mapW, wf, cg * 32, tap * 512 + kc * 64, 0);
                        if (++ws == WST) { ws = 0; wph ^= 1; }
                        const int it = kc * 5 + tap - 10;
                        if (it >= 0 && it < 16) {
                            const uint32_t wob = bars + 8 * BAR_WO;
                            if (it == 0) mbar_expect_tx(wob, WO_BYTES);
                            tma_load_2d(sb + SM_WO + (it & 1) * 65536 + (it >> 1) * 8192, &mapWo, wob, c4 * 128 + (it & 1) * 64, (it >> 1) * 64);
                        }
                    }
                }
            }
            __syncwarp();
        } else if (warp == 5) {
            unsigned int par = 0;
            if (lane == 0) par = (atomicAdd(&g_ticket, 1u) >> 7) & 1u;
            par = __shfl_sync(0xffffffffu, par, 0);
            __nanosleep(1500);
            uint4* mine = &g_zx[par][tt * 4 * 4096 + q * 1024 + 2 * c4 * 32];
#pragma unroll 1
            for (int i = 0; i < 32; i++) {
                mine[(i >> 3) * 4096 + ((i >> 1) & 3) * 256 + (i & 1) * 32 + lane] = make_uint4(0u, 0u, 0u, 0u);
                __nanosleep(100);
            }
            __syncwarp();
            if (lane == 0) {
                asm volatile("st.shared.u32 [%0], %1;" ::"r"(sb + SM_PAR), "r"(par) : "memory");
                mbar_arrive(bars + 8 * BAR_PAR);
            }
            uint4* clr = &g_zx[par ^ 1][blockIdx.x * 1024];
#pragma unroll 1
            for (int i = 0; i < 32; i++) {
                clr[i * 32 + lane] = make_uint4(0u, 0u, 0u, 0u);
                __nanosleep(64);
            }
        }
        mbar_wait(bars + 8 * BAR_PAR, 0);
        uint32_t par;
        asm volatile("ld.shared.u32 %0, [%1];" : "=r"(par) : "r"(sb + SM_PAR) : "memory");
        const uint8_t* zsrc = reinterpret_cast<const uint8_t*>(&g_zx[par][(tt * 4 + q) * 4096]);
        fetch_slot(7 - warp, sb, zsrc, q, lane);
    } else {
        float acc[128];
#pragma unroll
        for (int i = 0; i < 128; i++) acc[i] = 0.f;
        uint32_t afr[2][4][4];
        const int lk = ((lane >> 4) << 3) + (lane & 7);
        const uint32_t a_lane_off = ((lane >> 3) & 1) * 4096 + lk * 64 + ((warp ^ ((lk >> 1) & 3)) << 4);
        int ws = 0, wph = 0;
        uint32_t par = 0;
        if (threadIdx.x == 0) PROF(1);
#pragma unroll 1
        for (int kc2 = 0; kc2 < 4; kc2++) {
#pragma unroll
            for (int u = 0; u < 10; u++) {
                const int xs = u / 5;
                const int tap = u % 5;
                if (u == 5 && kc2 == 3) break;
                if (tap == 0) mbar_wait(bars + 8 * (BAR_XFULL + xs), kc2 & 1);
                mbar_wait(bars + 8 * (BAR_WFULL + ws), wph);
                if (kc2 == 0 && u == 0 && threadIdx.x == 0) PROF(2);
                const uint32_t wa = sb + SM_W + ws * WBYTES + a_lane_off;
                load_w_frags(afr[u & 1], wa);
                __syncwarp();
                if (lane == 0) mbar_arrive(bars + 8 * (BAR_WEMPTY + ws));
                if (++ws == WST) { ws = 0; wph ^= 1; }
                const uint64_t db = make_desc(sb + SM_X + xs * XBYTES + (8 - 2 * tap) * 128, 16, 1024);
#pragma unroll
                for (int h = 0; h < MS; h++) {
#pragma unroll
                    for (int kk = h * (4 / MS); kk < (h + 1) * (4 / MS); kk++) scale_w_frag(afr[u & 1][kk]);
                    wgmma_fence();
#pragma unroll
                    for (int kk = h * (4 / MS); kk < (h + 1) * (4 / MS); kk++) {
                        wgmma_m64n128k16_rs_half<0>(acc, afr[u & 1][kk], db + kk * 2);
                        wgmma_m64n128k16_rs_half<64>(acc, afr[u & 1][kk], db + kk * 2 + 1024);
                    }
                    wgmma_commit();
                }
                if (u == 2 && kc2 == 3) {
                    mbar_wait(bars + 8 * BAR_PAR, 0);
                    asm volatile("ld.shared.u32 %0, [%1];" : "=r"(par) : "r"(sb + SM_PAR) : "memory");
                    mbar_wait(bars + 8 * BAR_WO, 0);
                }
                wgmma_wait<MS>();
                if (tap == 0 && (u > 0 || kc2 > 0)) {
                    if (lane == 0) mbar_arrive(bars + 8 * (BAR_XEMPTY + (xs ^ 1)));
                }
            }
        }
        uint8_t* zx = reinterpret_cast<uint8_t*>(&g_zx[par][tt * 4 * 4096]);
        uint8_t* zdst = zx + q * 16384 + (2 * c4 + (warp >> 1)) * 512 + (warp & 1) * 256 +
                        ((lane >> 1) & 1) * 4096 + (lane & 1) * 128 + (lane >> 2) * 16;
        switch (q) {
            case 0: tail_gemm1<0>(acc, afr, sb, ws, wph, a_lane_off, zdst, lane, zero); break;
            case 1: tail_gemm1<1>(acc, afr, sb, ws, wph, a_lane_off, zdst, lane, zero); break;
            case 2: tail_gemm1<2>(acc, afr, sb, ws, wph, a_lane_off, zdst, lane, zero); break;
            default: tail_gemm1<3>(acc, afr, sb, ws, wph, a_lane_off, zdst, lane, zero); break;
        }
        if (threadIdx.x == 0) PROF(4);

        float acc2[64], acc3a[32], acc3b[32];
#pragma unroll
        for (int i = 0; i < 64; i++) acc2[i] = 0.f;
        const uint32_t stg = sb + SM_OSTG + warp * 4096;
        const int tok0 = t0 + q * 64 + (warp >> 1) * 32 + (warp & 1) * 4 + (lane >> 4) * 8 + ((lane >> 3) & 1);
        const __nv_bfloat16* orow = out + ((size_t)batch * T_LEN + tok0) * D_CH + c4 * 128 + (lane & 7) * 8;
        uint32_t bad;
        {
            uint32_t za[3][8][4];
            z_load<0>(za[0], sb, warp, lane);
            if (threadIdx.x == 0) PROF(12);
            z_issue(acc2, za[0], sb, q ^ 0);
            z_load<1>(za[1], sb, warp, lane);
            bad = z_check(za[0]) ? 0u : 1u;
            if (threadIdx.x == 0) PROF(13);
            z_issue(acc2, za[1], sb, q ^ 1);
            z_load<2>(za[2], sb, warp, lane);
            bad |= z_check(za[1]) ? 0u : 2u;
            if (threadIdx.x == 0) PROF(14);
            z_issue(acc2, za[2], sb, q ^ 2);
            wgmma_wait<2 * HS>();
            z_load<3>(za[0], sb, warp, lane);
            bad |= z_check(za[2]) ? 0u : 4u;
            if (threadIdx.x == 0) PROF(15);
            const uint64_t db = make_desc(sb + SM_WO + (q ^ 3) * 16384, 65536, 1024);
#pragma unroll
            for (int h = 0; h < HS3; h++) {
#pragma unroll
                for (int j = h * (8 / HS3); j < (h + 1) * (8 / HS3); j++)
                    asm volatile("" : "+r"(za[0][j][0]), "+r"(za[0][j][1]), "+r"(za[0][j][2]), "+r"(za[0][j][3]) :: "memory");
                wgmma_fence();
#pragma unroll
                for (int j = h * (8 / HS3); j < (h + 1) * (8 / HS3); j++) wgmma_m64n64k16_rs(acc3a, za[0][j], db + j * 128, j);
                wgmma_commit();
            }
#pragma unroll
            for (int j = 0; j < 8; j++) wgmma_m64n64k16_rs(acc3b, za[0][j], db + j * 128 + 4096, j);
            wgmma_commit();
            wgmma_wait<1>();
            fence_regs(acc2);
            fence_regs(acc3a);
            if (threadIdx.x == 0) PROF(10);
            store_half<0>(acc2, acc3a, stg, orow, tok0, lane);
            sched_fence<7>(zero);
            bad |= z_check(za[0]) ? 0u : 8u;
        }
        wgmma_wait<0>();
        fence_regs(acc3b);
        store_half<1>(acc2, acc3b, stg, orow, tok0, lane);
        if (__builtin_expect(wg_any(bad != 0u), 0)) {
            const uint8_t* zsrc = zx + q * 65536 + warp * 4096;
            uint32_t rph = 0;
            z_repair<0>(acc2, sb, zsrc + (q ^ 0) * 16384, q ^ 0, warp, lane, bad & 1u, rph);
            z_repair<1>(acc2, sb, zsrc + (q ^ 1) * 16384, q ^ 1, warp, lane, bad & 2u, rph);
            z_repair<2>(acc2, sb, zsrc + (q ^ 2) * 16384, q ^ 2, warp, lane, bad & 4u, rph);
            z_repair<3>(acc2, sb, zsrc + (q ^ 3) * 16384, q ^ 3, warp, lane, bad & 8u, rph);
            fence_regs(acc2);
            __syncwarp();
            store_half<0>(acc2, acc3a, stg, orow, tok0, lane);
            store_half<1>(acc2, acc3b, stg, orow, tok0, lane);
        }
        if (threadIdx.x == 0) PROFG(11);
    }
}

typedef CUresult (*EncodeFn)(CUtensorMap*, CUtensorMapDataType, cuuint32_t, void*, const cuuint64_t*, const cuuint64_t*,
                             const cuuint32_t*, const cuuint32_t*, CUtensorMapInterleave, CUtensorMapSwizzle,
                             CUtensorMapL2promotion, CUtensorMapFloatOOBfill);

void encode(EncodeFn fn, CUtensorMap* m, const void* ptr, int rank, const cuuint64_t* dims, const cuuint64_t* strides,
            const cuuint32_t* box, CUtensorMapSwizzle sw) {
    cuuint32_t es[3] = {1, 1, 1};
    fn(m, CU_TENSOR_MAP_DATA_TYPE_BFLOAT16, rank, const_cast<void*>(ptr), dims, strides, box, es,
       CU_TENSOR_MAP_INTERLEAVE_NONE, sw, CU_TENSOR_MAP_L2_PROMOTION_L2_128B, CU_TENSOR_MAP_FLOAT_OOB_FILL_NONE);
}

}

extern "C" void kernel_launch(void* const* d_in, const int* in_sizes, int n_in, void* d_out, int out_size) {
    (void)in_sizes; (void)n_in; (void)out_size;
    static EncodeFn enc = nullptr;
    if (!enc) {
        void* fn = nullptr;
        cudaDriverEntryPointQueryResult qr;
        cudaGetDriverEntryPoint("cuTensorMapEncodeTiled", &fn, cudaEnableDefault, &qr);
        enc = (EncodeFn)fn;
        cudaFuncSetAttribute(wavenet_fused_kernel, cudaFuncAttributeMaxDynamicSharedMemorySize, SM_TOTAL);
    }
    CUtensorMap mX, mW, mWo;
    {
        cuuint64_t dims[3] = {512, (cuuint64_t)T_LEN, 2}, str[2] = {1024, (cuuint64_t)T_LEN * 1024};
        cuuint32_t box[3] = {64, XBOX, 1};
        encode(enc, &mX, d_in[0], 3, dims, str, box, CU_TENSOR_MAP_SWIZZLE_128B);
    }
    {
        cuuint64_t dims[3] = {512, 2560, 2}, str[2] = {2048, 1024};
        cuuint32_t box[3] = {32, 64, 2};
        encode(enc, &mW, d_in[1], 3, dims, str, box, CU_TENSOR_MAP_SWIZZLE_64B);
    }
    {
        cuuint64_t dims[2] = {512, 512}, str[1] = {1024};
        cuuint32_t box[2] = {64, 64};
        encode(enc, &mWo, d_in[2], 2, dims, str, box, CU_TENSOR_MAP_SWIZZLE_128B);
    }
    wavenet_fused_kernel<<<128, NTHREADS, SM_TOTAL>>>(mX, mW, mWo, (__nv_bfloat16*)d_out, 0u);
}
```

```cpp
#include <cuda_runtime.h>
#include <cuda_bf16.h>
#include <cuda.h>
#include <stdint.h>

namespace {

constexpr int T_LEN   = 1000;
constexpr int D_CH    = 512;
constexpr int NTOK    = 256;
constexpr int XROWS   = NTOK + 8;
constexpr int XBYTES  = XROWS * 128;
constexpr int XBOX    = 88;
constexpr int XST     = 2;
constexpr int WST     = 4;
constexpr int WBYTES  = 8192;
constexpr int WO_BYTES = 131072;

constexpr int SM_WO   = 0;
constexpr int SM_X    = SM_WO + WO_BYTES;
constexpr int SM_W    = SM_X + XST * XBYTES;
constexpr int SM_BAR  = SM_W + WST * WBYTES;
constexpr int SM_TOTAL = SM_BAR + 256;
__host__ __device__ constexpr int sm_zin(int i) { return SM_X + (i >> 1) * XBYTES + (i & 1) * 16384; }
constexpr int SM_OSTG  = SM_W;
constexpr int SM_ZFIX  = SM_W + 16384;

constexpr int BAR_WFULL  = 0;
constexpr int BAR_WEMPTY = BAR_WFULL + WST;
constexpr int BAR_XFULL  = BAR_WEMPTY + WST;
constexpr int BAR_XEMPTY = BAR_XFULL + XST;
constexpr int BAR_WO     = BAR_XEMPTY + XST;
constexpr int BAR_PAR    = BAR_WO + 1;
constexpr int BAR_Z      = BAR_PAR + 1;
constexpr int BAR_RETRY  = BAR_Z + 4;

constexpr int SM_PAR   = SM_BAR + 240;
constexpr int NTHREADS = 256;
constexpr int MS = 2;
constexpr int AS = 2;
constexpr int HS = 4;
constexpr int HS3 = 4;
#define ZDELAY0 650
#define ZDELAY1 600
#define ZDELAY2 650
#define ZDELAY3 600

__device__ uint4 g_zx[2][8 * 4 * 4096];
__device__ unsigned int g_ticket;

#define PROF(i)
#define PROFG(i)

__device__ __forceinline__ uint32_t smem_u32(const void* p) { return (uint32_t)__cvta_generic_to_shared(p); }

__device__ __forceinline__ void mbar_init(uint32_t bar, uint32_t cnt) {
    asm volatile("mbarrier.init.shared::cta.b64 [%0], %1;" ::"r"(bar), "r"(cnt));
}
__device__ __forceinline__ void mbar_expect_tx(uint32_t bar, uint32_t bytes) {
    asm volatile("mbarrier.arrive.expect_tx.shared::cta.b64 _, [%0], %1;" ::"r"(bar), "r"(bytes) : "memory");
}
__device__ __forceinline__ void mbar_arrive(uint32_t bar) {
    asm volatile("mbarrier.arrive.shared::cta.b64 _, [%0];" ::"r"(bar) : "memory");
}
__device__ __forceinline__ void mbar_wait(uint32_t bar, uint32_t parity) {
    asm volatile(
        "{\n"
        ".reg .pred p;\n"
        "WAIT_LOOP:\n"
        "mbarrier.try_wait.parity.shared::cta.b64 p, [%0], %1;\n"
        "@p bra WAIT_DONE;\n"
        "bra WAIT_LOOP;\n"
        "WAIT_DONE:\n"
        "}\n" ::"r"(bar), "r"(parity) : "memory");
}
__device__ __forceinline__ void tma_load_3d(uint32_t dst, const CUtensorMap* m, uint32_t bar, int c0, int c1, int c2) {
    asm volatile("cp.async.bulk.tensor.3d.shared::cluster.global.mbarrier::complete_tx::bytes [%0], [%1, {%3, %4, %5}], [%2];"
                 ::"r"(dst), "l"(m), "r"(bar), "r"(c0), "r"(c1), "r"(c2) : "memory");
}
__device__ __forceinline__ void tma_load_2d(uint32_t dst, const CUtensorMap* m, uint32_t bar, int c0, int c1) {
    asm volatile("cp.async.bulk.tensor.2d.shared::cluster.global.mbarrier::complete_tx::bytes [%0], [%1, {%3, %4}], [%2];"
                 ::"r"(dst), "l"(m), "r"(bar), "r"(c0), "r"(c1) : "memory");
}
__device__ __forceinline__ void prefetch_tmap(const CUtensorMap* m) {
    asm volatile("prefetch.tensormap [%0];" ::"l"(m) : "memory");
}
__device__ __forceinline__ void wgmma_fence() { asm volatile("wgmma.fence.sync.aligned;" ::: "memory"); }
__device__ __forceinline__ void wgmma_commit() { asm volatile("wgmma.commit_group.sync.aligned;" ::: "memory"); }
template <int N> __device__ __forceinline__ void wgmma_wait() {
    asm volatile("wgmma.wait_group.sync.aligned %0;" ::"n"(N) : "memory");
}
template <int N> __device__ __forceinline__ void fence_regs(float (&d)[N]) {
#pragma unroll
    for (int i = 0; i < N; i++) asm volatile("" : "+f"(d[i]) :: "memory");
}
__device__ __forceinline__ void ldsm_x4_trans(uint32_t (&r)[4], uint32_t addr) {
    asm volatile("ldmatrix.sync.aligned.m8n8.x4.trans.shared.b16 {%0, %1, %2, %3}, [%4];"
                 : "=r"(r[0]), "=r"(r[1]), "=r"(r[2]), "=r"(r[3]) : "r"(addr) : "memory");
}
__device__ __forceinline__ void stsm_x4(uint32_t addr, uint32_t a, uint32_t b, uint32_t c, uint32_t d) {
    asm volatile("stmatrix.sync.aligned.m8n8.x4.shared.b16 [%0], {%1, %2, %3, %4};"
                 ::"r"(addr), "r"(a), "r"(b), "r"(c), "r"(d) : "memory");
}
__device__ __forceinline__ void st_relaxed_v4(void* p, uint32_t a, uint32_t b, uint32_t c, uint32_t d) {
    asm volatile("st.relaxed.gpu.global.v4.b32 [%0], {%1, %2, %3, %4};" ::"l"(p), "r"(a), "r"(b), "r"(c), "r"(d) : "memory");
}
__device__ __forceinline__ void bulk_load(uint32_t dst, const void* src, uint32_t bytes, uint32_t bar) {
    asm volatile("cp.async.bulk.shared::cluster.global.mbarrier::complete_tx::bytes [%0], [%1], %2, [%3];"
                 ::"r"(dst), "l"(src), "r"(bytes), "r"(bar) : "memory");
}
__device__ __forceinline__ uint32_t clock_now() {
    uint32_t t;
    asm volatile("mov.u32 %0, %%clock;" : "=r"(t) :: "memory");
    return t;
}
template <int BIT>
__device__ __forceinline__ void sched_fence(uint32_t zero) {
    asm volatile("{\n.reg .pred p;\n.reg .b32 t;\nand.b32 t, %0, %1;\nsetp.eq.u32 p, t, 0;\n@p bra SF_DONE;\ntrap;\nSF_DONE:\n}\n"
                 ::"r"(zero), "n"(1u << BIT) : "memory");
}
__device__ __forceinline__ float tanh_fast(float x) {
    float y;
    asm volatile("tanh.approx.f32 %0, %1;" : "=f"(y) : "f"(x));
    return y;
}
__device__ __forceinline__ void load_w_frags(uint32_t (&f)[4][4], uint32_t wa) {
#pragma unroll
    for (int kk = 0; kk < 4; kk++) ldsm_x4_trans(f[kk], wa + kk * 1024);
}
__device__ __forceinline__ void scale_w_frag(uint32_t (&f)[4]) {
    asm volatile("mul.rn.bf16x2 %0, %0, %1;" : "+r"(f[1]) : "r"(0x3F003F00u));
    asm volatile("mul.rn.bf16x2 %0, %0, %1;" : "+r"(f[3]) : "r"(0x3F003F00u));
}
__device__ __forceinline__ uint32_t pack_bf16(float lo, float hi) {
    uint32_t r;
    asm("cvt.rn.bf16x2.f32 %0, %1, %2;" : "=r"(r) : "f"(hi), "f"(lo));
    return r;
}
__device__ __forceinline__ uint64_t make_desc(uint32_t addr, uint32_t lbo_bytes, uint32_t sbo_bytes) {
    return (uint64_t)((addr & 0x3FFFF) >> 4) | ((uint64_t)(lbo_bytes >> 4) << 16) | ((uint64_t)(sbo_bytes >> 4) << 32) |
           ((uint64_t)1 << 62);
}

#define R8(d, o) "+f"(d[o + 0]), "+f"(d[o + 1]), "+f"(d[o + 2]), "+f"(d[o + 3]), "+f"(d[o + 4]), "+f"(d[o + 5]), "+f"(d[o + 6]), "+f"(d[o + 7])

__device__ __forceinline__ void wgmma_m64n128k16_rs(float (&d)[64], const uint32_t (&a)[4], uint64_t descB) {
    asm volatile(
        "wgmma.mma_async.sync.aligned.m64n128k16.f32.bf16.bf16 "
        "{%0, %1, %2, %3, %4, %5, %6, %7, %8, %9, %10, %11, %12, %13, %14, %15, "
        "%16, %17, %18, %19, %20, %21, %22, %23, %24, %25, %26, %27, %28, %29, %30, %31, "
        "%32, %33, %34, %35, %36, %37, %38, %39, %40, %41, %42, %43, %44, %45, %46, %47, "
        "%48, %49, %50, %51, %52, %53, %54, %55, %56, %57, %58, %59, %60, %61, %62, %63}, "
        "{%64, %65, %66, %67}, %68, 1, -1, 1, 1;\n"
        : R8(d, 0), R8(d, 8), R8(d, 16), R8(d, 24), R8(d, 32), R8(d, 40), R8(d, 48), R8(d, 56)
        : "r"(a[0]), "r"(a[1]), "r"(a[2]), "r"(a[3]), "l"(descB));
}

__device__ __forceinline__ void wgmma_m64n64k16_rs(float (&d)[32], const uint32_t (&a)[4], uint64_t descB, int scale_d) {
    asm volatile(
        "{\n"
        ".reg .pred p;\n"
        "setp.ne.b32 p, %37, 0;\n"
        "wgmma.mma_async.sync.aligned.m64n64k16.f32.bf16.bf16 "
        "{%0, %1, %2, %3, %4, %5, %6, %7, %8, %9, %10, %11, %12, %13, %14, %15, "
        "%16, %17, %18, %19, %20, %21, %22, %23, %24, %25, %26, %27, %28, %29, %30, %31}, "
        "{%32, %33, %34, %35}, %36, p, -1, 1, 1;\n"
        "}\n"
        : R8(d, 0), R8(d, 8), R8(d, 16), R8(d, 24)
        : "r"(a[0]), "r"(a[1]), "r"(a[2]), "r"(a[3]), "l"(descB), "r"(scale_d));
}

template <int OFF>
__device__ __forceinline__ void wgmma_m64n128k16_rs_half(float (&d)[128], const uint32_t (&a)[4], uint64_t descB) {
    asm volatile(
        "wgmma.mma_async.sync.aligned.m64n128k16.f32.bf16.bf16 "
        "{%0, %1, %2, %3, %4, %5, %6, %7, %8, %9, %10, %11, %12, %13, %14, %15, "
        "%16, %17, %18, %19, %20, %21, %22, %23, %24, %25, %26, %27, %28, %29, %30, %31, "
        "%32, %33, %34, %35, %36, %37, %38, %39, %40, %41, %42, %43, %44, %45, %46, %47, "
        "%48, %49, %50, %51, %52, %53, %54, %55, %56, %57, %58, %59, %60, %61, %62, %63}, "
        "{%64, %65, %66, %67}, %68, 1, 1, 1, 0;\n"
        : R8(d, OFF + 0), R8(d, OFF + 8), R8(d, OFF + 16), R8(d, OFF + 24), R8(d, OFF + 32), R8(d, OFF + 40), R8(d, OFF + 48), R8(d, OFF + 56)
        : "r"(a[0]), "r"(a[1]), "r"(a[2]), "r"(a[3]), "l"(descB));
}
template <int OFF> __device__ __forceinline__ void fence_half(float (&d)[128]) {
#pragma unroll
    for (int i = 0; i < 64; i++) asm volatile("" : "+f"(d[OFF + i]) :: "memory");
}

template <int Q0, int N> struct GateGroup { static constexpr int J = 2 * (Q0 ^ (N >> 1)) + (N & 1); };

template <int Q0, int N>
__device__ __forceinline__ void gate_mufu(float (&acc)[128]) {
    constexpr int J = GateGroup<Q0, N>::J;
#pragma unroll
    for (int i = 0; i < 16; i++) acc[16 * J + i] = tanh_fast(acc[16 * J + i]);
}
template <int Q0, int N>
__device__ __forceinline__ void gate_finish(float (&acc)[128], uint8_t* zdst) {
    constexpr int J = GateGroup<Q0, N>::J;
    uint32_t zp[4];
#pragma unroll
    for (int i = 0; i < 4; i++) {
        const int r = 16 * J + 4 * i;
        zp[i] = __vmaxu2(pack_bf16(acc[r] * fmaf(acc[r + 2], -0.5f, -0.5f), acc[r + 1] * fmaf(acc[r + 3], -0.5f, -0.5f)), 0x00010001u);
    }
    st_relaxed_v4(zdst + (J >> 1) * 65536 + (J & 1) * 8192, zp[0], zp[1], zp[2], zp[3]);
    if (N & 1) asm volatile("bar.arrive %0, 160;" ::"n"(2 + (N >> 1)) : "memory");
}

template <int Q0>
__device__ __forceinline__ void tail_gemm1(float (&acc)[128], uint32_t (&afr)[2][4][4], uint32_t sb, int ws, int wph, uint32_t a_lane_off,
                                           uint8_t* zdst, int lane, uint32_t zero) {
    constexpr int OA = (Q0 >> 1) * 64;
    constexpr int OB = 64 - OA;
    const uint32_t bars = sb + SM_BAR;
    uint32_t fa[4][4], fb[4][4], fc[4][4];
    const int ws0 = ws;
    auto wtile = [&](int tap) { return sb + SM_W + ((ws0 + tap) & (WST - 1)) * WBYTES + a_lane_off; };
    auto wwait = [&](int tap) {
        const int st = ws0 + tap;
        mbar_wait(bars + 8 * (BAR_WFULL + (st & (WST - 1))), wph ^ ((st >> 2) & 1));
    };
    auto load = [&](uint32_t (&f)[4][4], int tap) { load_w_frags(f, wtile(tap)); };
    auto issueA = [&](uint32_t (&f)[4][4], int tap) {
        const uint64_t db = make_desc(sb + SM_X + XBYTES + (8 - 2 * tap) * 128 + OA * 256, 16, 1024);
#pragma unroll
        for (int h = 0; h < AS; h++) {
#pragma unroll
            for (int kk = h * (4 / AS); kk < (h + 1) * (4 / AS); kk++) scale_w_frag(f[kk]);
            wgmma_fence();
#pragma unroll
            for (int kk = h * (4 / AS); kk < (h + 1) * (4 / AS); kk++) wgmma_m64n128k16_rs_half<OA>(acc, f[kk], db + kk * 2);
            wgmma_commit();
        }
    };
    auto issueB = [&](uint32_t (&f)[4][4], int tap) {
        const uint64_t db = make_desc(sb + SM_X + XBYTES + (8 - 2 * tap) * 128 + OB * 256, 16, 1024);
        wgmma_fence();
#pragma unroll
        for (int kk = 0; kk < 4; kk++) wgmma_m64n128k16_rs_half<OB>(acc, f[kk], db + kk * 2);
        wgmma_commit();
    };
    mbar_wait(bars + 8 * (BAR_XFULL + 1), 1);
    wwait(0); load(fa, 0);
    __syncwarp();
    if (lane == 0) mbar_arrive(bars + 8 * (BAR_WEMPTY + ws0));
    wwait(1); load(fb, 1);
    wwait(2); load(fc, 2);
    issueA(fa, 0); wgmma_wait<AS>();
    wwait(3); load(afr[0], 3);
    issueA(fb, 1);
    issueA(fc, 2);
    wwait(4); load(afr[1], 4);
    issueA(afr[0], 3);
    issueA(afr[1], 4);
    if (threadIdx.x == 0) PROF(24);
    issueB(fa, 0);
    issueB(fb, 1);
    wgmma_wait<2>();
    fence_half<OA>(acc);
    sched_fence<0>(zero);
    gate_mufu<Q0, 0>(acc); gate_mufu<Q0, 1>(acc);
    gate_finish<Q0, 0>(acc, zdst); gate_finish<Q0, 1>(acc, zdst);
    sched_fence<1>(zero);
    issueB(fc, 2);
    issueB(afr[0], 3);
    sched_fence<2>(zero);
    gate_mufu<Q0, 2>(acc); gate_mufu<Q0, 3>(acc);
    sched_fence<3>(zero);
    issueB(afr[1], 4);
    sched_fence<4>(zero);
    gate_finish<Q0, 2>(acc, zdst); gate_finish<Q0, 3>(acc, zdst);
    wgmma_wait<0>();
    fence_half<OB>(acc);
    if (threadIdx.x == 0) PROF(3);
    gate_mufu<Q0, 4>(acc);
    gate_mufu<Q0, 5>(acc);
    gate_finish<Q0, 4>(acc, zdst);
    gate_finish<Q0, 5>(acc, zdst);
    sched_fence<5>(zero);
    gate_mufu<Q0, 6>(acc);
    gate_mufu<Q0, 7>(acc);
    gate_finish<Q0, 6>(acc, zdst);
    gate_finish<Q0, 7>(acc, zdst);
}

__device__ __forceinline__ void fetch_slot(int i, uint32_t sb, const uint8_t* zsrc, int q, int lane) {
    const uint32_t bars = sb + SM_BAR;
    asm volatile("bar.sync %0, 160;" ::"r"(2 + i) : "memory");
    if (lane == 0) {
        uint32_t t;
        asm volatile("mov.u32 %0, %%clock;" : "=r"(t) : "r"(lane) : "memory");
        const uint32_t delay = (i == 0) ? ZDELAY0 : (i == 1) ? ZDELAY1 : (i == 2) ? ZDELAY2 : ZDELAY3;
        while (clock_now() - t < delay) {}
        mbar_expect_tx(bars + 8 * (BAR_Z + i), 16384);
        bulk_load(sb + sm_zin(i), zsrc + (q ^ i) * 16384, 16384, bars + 8 * (BAR_Z + i));
        PROF(26 + i);
    }
    __syncwarp();
}

template <int I>
__device__ __forceinline__ void z_load(uint32_t (&z)[8][4], uint32_t sb, int warp, int lane) {
    mbar_wait(sb + SM_BAR + 8 * (BAR_Z + I), 0);
#pragma unroll
    for (int j = 0; j < 8; j++) ldsm_x4_trans(z[j], sb + sm_zin(I) + warp * 4096 + j * 512 + lane * 16);
}
__device__ __forceinline__ bool z_check(const uint32_t (&z)[8][4]) {
    uint32_t m0 = 0xFFFFFFFFu, m1 = 0xFFFFFFFFu;
#pragma unroll
    for (int j = 0; j < 8; j++) {
        m0 = __vimin3_u16x2(m0, z[j][0], z[j][1]);
        m1 = __vimin3_u16x2(m1, z[j][2], z[j][3]);
    }
    m0 = __vminu2(m0, m1);
    return __all_sync(0xffffffffu, ((m0 & 0xFFFFu) != 0u) && ((m0 >> 16) != 0u));
}
__device__ __forceinline__ void z_issue(float (&acc2)[64], uint32_t (&z)[8][4], uint32_t sb, int beta) {
    const uint64_t db = make_desc(sb + SM_WO + beta * 16384, 65536, 1024);
#pragma unroll
    for (int h = 0; h < HS; h++) {
#pragma unroll
        for (int j = h * (8 / HS); j < (h + 1) * (8 / HS); j++)
            asm volatile("" : "+r"(z[j][0]), "+r"(z[j][1]), "+r"(z[j][2]), "+r"(z[j][3]) :: "memory");
        wgmma_fence();
#pragma unroll
        for (int j = h * (8 / HS); j < (h + 1) * (8 / HS); j++) wgmma_m64n128k16_rs(acc2, z[j], db + j * 128);
        wgmma_commit();
    }
}
__device__ __forceinline__ bool wg_any(bool p) {
    uint32_t r;
    asm volatile("{\n.reg .pred a, b;\nsetp.ne.u32 a, %1, 0;\nbarrier.cta.red.or.aligned.pred b, 1, 128, a;\nselp.u32 %0, 1, 0, b;\n}\n"
                 : "=r"(r) : "r"((uint32_t)p) : "memory");
    return r != 0;
}
template <int I>
__device__ __forceinline__ void z_repair(float (&acc2)[64], uint32_t sb, const uint8_t* src, int beta, int warp, int lane, uint32_t mine,
                                         uint32_t& rph) {
    if (!wg_any(mine != 0u)) return;
    uint32_t z[8][4];
    if (mine) {
        const uint32_t zo = sb + sm_zin(I) + warp * 4096;
        const uint32_t zs = sb + SM_ZFIX + warp * 4096;
        const uint32_t bar = sb + SM_BAR + 8 * (BAR_RETRY + warp);
        int spins = 0;
        do {
            __syncwarp();
            if (lane == 0) {
                mbar_expect_tx(bar, 4096);
                bulk_load(zs, src, 4096, bar);
            }
            mbar_wait(bar, rph);
            rph ^= 1;
#pragma unroll
            for (int j = 0; j < 8; j++) ldsm_x4_trans(z[j], zs + j * 512 + lane * 16);
        } while (!z_check(z) && ++spins < (1 << 16));
#pragma unroll
        for (int j = 0; j < 8; j++) {
            uint32_t o[4];
            ldsm_x4_trans(o, zo + j * 512 + lane * 16);
#pragma unroll
            for (int k = 0; k < 4; k++) z[j][k] &= __vcmpeq2(o[k], 0u);
        }
    } else {
#pragma unroll
        for (int j = 0; j < 8; j++)
#pragma unroll
            for (int k = 0; k < 4; k++) z[j][k] = 0u;
    }
    z_issue(acc2, z, sb, beta);
    wgmma_wait<0>();
}

template <int H>
__device__ __forceinline__ void store_half(const float (&a)[64], const float (&b)[32], uint32_t stg, const __nv_bfloat16* orow, int tok0, int lane) {
    const uint32_t st = stg + H * 2048 + (lane & 15) * 128;
    const int csel = lane >> 4, sw = lane & 7;
#pragma unroll
    for (int j2 = 0; j2 < 4; j2++) {
        const int j = 2 * j2, o = 32 * H + 4 * j;
        const uint32_t r0 = pack_bf16(a[o + 0] + b[4 * j + 0], a[o + 1] + b[4 * j + 1]);
        const uint32_t r1 = pack_bf16(a[o + 2] + b[4 * j + 2], a[o + 3] + b[4 * j + 3]);
        const uint32_t r2 = pack_bf16(a[o + 4] + b[4 * j + 4], a[o + 5] + b[4 * j + 5]);
        const uint32_t r3 = pack_bf16(a[o + 6] + b[4 * j + 6], a[o + 7] + b[4 * j + 7]);
        stsm_x4(st + (((j + csel) ^ sw) << 4), r0, r1, r2, r3);
    }
    __syncwarp();
#pragma unroll
    for (int i = 0; i < 4; i++) {
        const int r = 4 * i + (lane >> 3);
        uint32_t v0, v1, v2, v3;
        asm volatile("ld.shared.v4.b32 {%0, %1, %2, %3}, [%4];" : "=r"(v0), "=r"(v1), "=r"(v2), "=r"(v3)
                     : "r"(stg + H * 2048 + r * 128 + (((lane & 7) ^ (r & 7)) << 4)) : "memory");
        const int dt = (i & 1) * 16 + (i >> 1) * 2;
        asm volatile("{\n.reg .pred p;\nsetp.lt.s32 p, %5, %6;\n@p st.global.v4.b32 [%0], {%1, %2, %3, %4};\n}\n"
                     ::"l"(orow + dt * D_CH + H * 64), "r"(v0), "r"(v1), "r"(v2), "r"(v3), "r"(tok0), "r"(T_LEN - dt) : "memory");
    }
}

__global__ void __launch_bounds__(NTHREADS, 1)
wavenet_fused_kernel(const __grid_constant__ CUtensorMap mapX, const __grid_constant__ CUtensorMap mapW,
                     const __grid_constant__ CUtensorMap mapWo, __nv_bfloat16* __restrict__ out, const uint32_t zero) {
    extern __shared__ __align__(1024) uint8_t smem_raw[];
    const uint32_t sb = smem_u32(smem_raw);
    const uint32_t bars = sb + SM_BAR;
    const int warp = threadIdx.x >> 5;
    const int lane = threadIdx.x & 31;
    const int cg = blockIdx.x & 15;
    const int tt = blockIdx.x >> 4;
    const int batch = tt >> 2;
    const int t0 = (tt & 3) * NTOK;
    const int c4 = cg & 3, q = cg >> 2;

    if (threadIdx.x == 128) {
        PROFG(0);
        const uint32_t xf = bars + 8 * BAR_XFULL;
        mbar_init(bars + 8 * BAR_WFULL, 1);
        mbar_expect_tx(bars + 8 * BAR_WFULL, WBYTES);
        tma_load_3d(sb + SM_W, &mapW, bars + 8 * BAR_WFULL, cg * 32, 0, 0);
        mbar_init(xf, 1);
        mbar_expect_tx(xf, XBYTES);
#pragma unroll
        for (int j = 0; j < 3; j++) tma_load_3d(sb + SM_X + j * XBOX * 128, &mapX, xf, 0, t0 - 8 + j * XBOX, batch);
#pragma unroll
        for (int i = 1; i < WST; i++) {
            mbar_init(bars + 8 * (BAR_WFULL + i), 1);
            mbar_expect_tx(bars + 8 * (BAR_WFULL + i), WBYTES);
            tma_load_3d(sb + SM_W + i * WBYTES, &mapW, bars + 8 * (BAR_WFULL + i), cg * 32, i * 512, 0);
        }
        asm volatile("fence.mbarrier_init.release.cluster;" ::: "memory");
    }
    if (threadIdx.x == 160) prefetch_tmap(&mapX);
    if (threadIdx.x == 0) {
        for (int i = 0; i < WST; i++) mbar_init(bars + 8 * (BAR_WEMPTY + i), 4);
        mbar_init(bars + 8 * (BAR_XFULL + 1), 1);
        for (int i = 0; i < XST; i++) mbar_init(bars + 8 * (BAR_XEMPTY + i), 4);
        mbar_init(bars + 8 * BAR_WO, 1);
        mbar_init(bars + 8 * BAR_PAR, 1);
        for (int i = 0; i < 4; i++) {
            mbar_init(bars + 8 * (BAR_Z + i), 1);
            mbar_init(bars + 8 * (BAR_RETRY + i), 1);
        }
        asm volatile("fence.mbarrier_init.release.cluster;" ::: "memory");
    }
    __syncthreads();

    if (warp >= 4) {
        if (warp == 4) {
            if (lane == 0) {
                int ws = 0, wph = 0;
                for (int kc = 0; kc < 8; kc++) {
                    const int xs = kc & 1;
                    if (kc > 0) {
                        mbar_wait(bars + 8 * (BAR_XEMPTY + xs), ((kc >> 1) & 1) ^ 1);
                        const uint32_t xf = bars + 8 * (BAR_XFULL + xs);
                        mbar_expect_tx(xf, XBYTES);
                        const uint32_t xd = sb + SM_X + xs * XBYTES;
#pragma unroll
                        for (int j = 0; j < 3; j++) tma_load_3d(xd + j * XBOX * 128, &mapX, xf, kc * 64, t0 - 8 + j * XBOX, batch);
                    } else {
                        prefetch_tmap(&mapWo);
                    }
                    for (int tap = (kc == 0 ? WST : 0); tap < 5; tap++) {
                        mbar_wait(bars + 8 * (BAR_WEMPTY + ws), wph);
                        const uint32_t wf = bars + 8 * (BAR_WFULL + ws);
                        mbar_expect_tx(wf, WBYTES);
                        tma_load_3d(sb + SM_W + ws * WBYTES, &mapW, wf, cg * 32, tap * 512 + kc * 64, 0);
                        if (++ws == WST) { ws = 0; wph ^= 1; }
                        const int it = kc * 5 + tap - 10;
                        if (it >= 0 && it < 16) {
                            const uint32_t wob = bars + 8 * BAR_WO;
                            if (it == 0) mbar_expect_tx(wob, WO_BYTES);
                            tma_load_2d(sb + SM_WO + (it & 1) * 65536 + (it >> 1) * 8192, &mapWo, wob, c4 * 128 + (it & 1) * 64, (it >> 1) * 64);
                        }
                    }
                }
            }
            __syncwarp();
        } else if (warp == 5) {
            unsigned int par = 0;
            if (lane == 0) par = (atomicAdd(&g_ticket, 1u) >> 7) & 1u;
            par = __shfl_sync(0xffffffffu, par, 0);
            __nanosleep(1500);
            uint4* mine = &g_zx[par][tt * 4 * 4096 + q * 1024 + 2 * c4 * 32];
#pragma unroll 1
            for (int i = 0; i < 32; i++) {
                mine[(i >> 3) * 4096 + ((i >> 1) & 3) * 256 + (i & 1) * 32 + lane] = make_uint4(0u, 0u, 0u, 0u);
                __nanosleep(100);
            }
            __syncwarp();
            if (lane == 0) {
                asm volatile("st.shared.u32 [%0], %1;" ::"r"(sb + SM_PAR), "r"(par) : "memory");
                mbar_arrive(bars + 8 * BAR_PAR);
            }
            uint4* clr = &g_zx[par ^ 1][blockIdx.x * 1024];
#pragma unroll 1
            for (int i = 0; i < 32; i++) {
                clr[i * 32 + lane] = make_uint4(0u, 0u, 0u, 0u);
                __nanosleep(64);
            }
        }
        mbar_wait(bars + 8 * BAR_PAR, 0);
        uint32_t par;
        asm volatile("ld.shared.u32 %0, [%1];" : "=r"(par) : "r"(sb + SM_PAR) : "memory");
        const uint8_t* zsrc = reinterpret_cast<const uint8_t*>(&g_zx[par][(tt * 4 + q) * 4096]);
        fetch_slot(7 - warp, sb, zsrc, q, lane);
    } else {
        float acc[128];
#pragma unroll
        for (int i = 0; i < 128; i++) acc[i] = 0.f;
        uint32_t afr[2][4][4];
        const int lk = ((lane >> 4) << 3) + (lane & 7);
        const uint32_t a_lane_off = ((lane >> 3) & 1) * 4096 + lk * 64 + ((warp ^ ((lk >> 1) & 3)) << 4);
        int ws = 0, wph = 0;
        uint32_t par = 0;
        if (threadIdx.x == 0) PROF(1);
#pragma unroll 1
        for (int kc2 = 0; kc2 < 4; kc2++) {
#pragma unroll
            for (int u = 0; u < 10; u++) {
                const int xs = u / 5;
                const int tap = u % 5;
                if (u == 5 && kc2 == 3) break;
                if (tap == 0) mbar_wait(bars + 8 * (BAR_XFULL + xs), kc2 & 1);
                mbar_wait(bars + 8 * (BAR_WFULL + ws), wph);
                if (kc2 == 0 && u == 0 && threadIdx.x == 0) PROF(2);
                const uint32_t wa = sb + SM_W + ws * WBYTES + a_lane_off;
                load_w_frags(afr[u & 1], wa);
                __syncwarp();
                if (lane == 0) mbar_arrive(bars + 8 * (BAR_WEMPTY + ws));
                if (++ws == WST) { ws = 0; wph ^= 1; }
                const uint64_t db = make_desc(sb + SM_X + xs * XBYTES + (8 - 2 * tap) * 128, 16, 1024);
#pragma unroll
                for (int h = 0; h < MS; h++) {
#pragma unroll
                    for (int kk = h * (4 / MS); kk < (h + 1) * (4 / MS); kk++) scale_w_frag(afr[u & 1][kk]);
                    wgmma_fence();
#pragma unroll
                    for (int kk = h * (4 / MS); kk < (h + 1) * (4 / MS); kk++) {
                        wgmma_m64n128k16_rs_half<0>(acc, afr[u & 1][kk], db + kk * 2);
                        wgmma_m64n128k16_rs_half<64>(acc, afr[u & 1][kk], db + kk * 2 + 1024);
                    }
                    wgmma_commit();
                }
                if (u == 2 && kc2 == 3) {
                    mbar_wait(bars + 8 * BAR_PAR, 0);
                    asm volatile("ld.shared.u32 %0, [%1];" : "=r"(par) : "r"(sb + SM_PAR) : "memory");
                    mbar_wait(bars + 8 * BAR_WO, 0);
                }
                wgmma_wait<MS>();
                if (tap == 0 && (u > 0 || kc2 > 0)) {
                    if (lane == 0) mbar_arrive(bars + 8 * (BAR_XEMPTY + (xs ^ 1)));
                }
            }
        }
        uint8_t* zx = reinterpret_cast<uint8_t*>(&g_zx[par][tt * 4 * 4096]);
        uint8_t* zdst = zx + q * 16384 + (2 * c4 + (warp >> 1)) * 512 + (warp & 1) * 256 +
                        ((lane >> 1) & 1) * 4096 + (lane & 1) * 128 + (lane >> 2) * 16;
        switch (q) {
            case 0: tail_gemm1<0>(acc, afr, sb, ws, wph, a_lane_off, zdst, lane, zero); break;
            case 1: tail_gemm1<1>(acc, afr, sb, ws, wph, a_lane_off, zdst, lane, zero); break;
            case 2: tail_gemm1<2>(acc, afr, sb, ws, wph, a_lane_off, zdst, lane, zero); break;
            default: tail_gemm1<3>(acc, afr, sb, ws, wph, a_lane_off, zdst, lane, zero); break;
        }
        if (threadIdx.x == 0) PROF(4);

        float acc2[64], acc3a[32], acc3b[32];
#pragma unroll
        for (int i = 0; i < 64; i++) acc2[i] = 0.f;
        const uint32_t stg = sb + SM_OSTG + warp * 4096;
        const int tok0 = t0 + q * 64 + (warp >> 1) * 32 + (warp & 1) * 4 + (lane >> 4) * 8 + ((lane >> 3) & 1);
        const __nv_bfloat16* orow = out + ((size_t)batch * T_LEN + tok0) * D_CH + c4 * 128 + (lane & 7) * 8;
        uint32_t bad;
        {
            uint32_t za[3][8][4];
            z_load<0>(za[0], sb, warp, lane);
            if (threadIdx.x == 0) PROF(12);
            z_issue(acc2, za[0], sb, q ^ 0);
            z_load<1>(za[1], sb, warp, lane);
            bad = z_check(za[0]) ? 0u : 1u;
            if (threadIdx.x == 0) PROF(13);
            z_issue(acc2, za[1], sb, q ^ 1);
            z_load<2>(za[2], sb, warp, lane);
            bad |= z_check(za[1]) ? 0u : 2u;
            if (threadIdx.x == 0) PROF(14);
            z_issue(acc2, za[2], sb, q ^ 2);
            wgmma_wait<2 * HS>();
            z_load<3>(za[0], sb, warp, lane);
            bad |= z_check(za[2]) ? 0u : 4u;
            if (threadIdx.x == 0) PROF(15);
            const uint64_t db = make_desc(sb + SM_WO + (q ^ 3) * 16384, 65536, 1024);
#pragma unroll
            for (int h = 0; h < HS3; h++) {
#pragma unroll
                for (int j = h * (8 / HS3); j < (h + 1) * (8 / HS3); j++)
                    asm volatile("" : "+r"(za[0][j][0]), "+r"(za[0][j][1]), "+r"(za[0][j][2]), "+r"(za[0][j][3]) :: "memory");
                wgmma_fence();
#pragma unroll
                for (int j = h * (8 / HS3); j < (h + 1) * (8 / HS3); j++) wgmma_m64n64k16_rs(acc3a, za[0][j], db + j * 128, j);
                wgmma_commit();
            }
#pragma unroll
            for (int j = 0; j < 8; j++) wgmma_m64n64k16_rs(acc3b, za[0][j], db + j * 128 + 4096, j);
            wgmma_commit();
            wgmma_wait<1>();
            fence_regs(acc2);
            fence_regs(acc3a);
            if (threadIdx.x == 0) PROF(10);
            store_half<0>(acc2, acc3a, stg, orow, tok0, lane);
            sched_fence<7>(zero);
            bad |= z_check(za[0]) ? 0u : 8u;
        }
        wgmma_wait<0>();
        fence_regs(acc3b);
        store_half<1>(acc2, acc3b, stg, orow, tok0, lane);
        if (__builtin_expect(wg_any(bad != 0u), 0)) {
            const uint8_t* zsrc = zx + q * 65536 + warp * 4096;
            uint32_t rph = 0;
            z_repair<0>(acc2, sb, zsrc + (q ^ 0) * 16384, q ^ 0, warp, lane, bad & 1u, rph);
            z_repair<1>(acc2, sb, zsrc + (q ^ 1) * 16384, q ^ 1, warp, lane, bad & 2u, rph);
            z_repair<2>(acc2, sb, zsrc + (q ^ 2) * 16384, q ^ 2, warp, lane, bad & 4u, rph);
            z_repair<3>(acc2, sb, zsrc + (q ^ 3) * 16384, q ^ 3, warp, lane, bad & 8u, rph);
            fence_regs(acc2);
            __syncwarp();
            store_half<0>(acc2, acc3a, stg, orow, tok0, lane);
            store_half<1>(acc2, acc3b, stg, orow, tok0, lane);
        }
        if (threadIdx.x == 0) PROFG(11);
    }
}

typedef CUresult (*EncodeFn)(CUtensorMap*, CUtensorMapDataType, cuuint32_t, void*, const cuuint64_t*, const cuuint64_t*,
                             const cuuint32_t*, const cuuint32_t*, CUtensorMapInterleave, CUtensorMapSwizzle,
                             CUtensorMapL2promotion, CUtensorMapFloatOOBfill);

void encode(EncodeFn fn, CUtensorMap* m, const void* ptr, int rank, const cuuint64_t* dims, const cuuint64_t* strides,
            const cuuint32_t* box, CUtensorMapSwizzle sw) {
    cuuint32_t es[3] = {1, 1, 1};
    fn(m, CU_TENSOR_MAP_DATA_TYPE_BFLOAT16, rank, const_cast<void*>(ptr), dims, strides, box, es,
       CU_TENSOR_MAP_INTERLEAVE_NONE, sw, CU_TENSOR_MAP_L2_PROMOTION_L2_128B, CU_TENSOR_MAP_FLOAT_OOB_FILL_NONE);
}

}

extern "C" void kernel_launch(void* const* d_in, const int* in_sizes, int n_in, void* d_out, int out_size) {
    (void)in_sizes; (void)n_in; (void)out_size;
    static EncodeFn enc = nullptr;
    if (!enc) {
        void* fn = nullptr;
        cudaDriverEntryPointQueryResult qr;
        cudaGetDriverEntryPoint("cuTensorMapEncodeTiled", &fn, cudaEnableDefault, &qr);
        enc = (EncodeFn)fn;
        cudaFuncSetAttribute(wavenet_fused_kernel, cudaFuncAttributeMaxDynamicSharedMemorySize, SM_TOTAL);
    }
    CUtensorMap mX, mW, mWo;
    {
        cuuint64_t dims[3] = {512, (cuuint64_t)T_LEN, 2}, str[2] = {1024, (cuuint64_t)T_LEN * 1024};
        cuuint32_t box[3] = {64, XBOX, 1};
        encode(enc, &mX, d_in[0], 3, dims, str, box, CU_TENSOR_MAP_SWIZZLE_128B);
    }
    {
        cuuint64_t dims[3] = {512, 2560, 2}, str[2] = {2048, 1024};
        cuuint32_t box[3] = {32, 64, 2};
        encode(enc, &mW, d_in[1], 3, dims, str, box, CU_TENSOR_MAP_SWIZZLE_64B);
    }
    {
        cuuint64_t dims[2] = {512, 512}, str[1] = {1024};
        cuuint32_t box[2] = {64, 64};
        encode(enc, &mWo, d_in[2], 2, dims, str, box, CU_TENSOR_MAP_SWIZZLE_128B);
    }
    wavenet_fused_kernel<<<128, NTHREADS, SM_TOTAL>>>(mX, mW, mWo, (__nv_bfloat16*)d_out, 0u);
}
```

```cpp
#include <cuda_runtime.h>
#include <cuda_bf16.h>
#include <cuda.h>
#include <stdint.h>

namespace {

constexpr int T_LEN   = 1000;
constexpr int D_CH    = 512;
constexpr int NTOK    = 256;
constexpr int XROWS   = NTOK + 8;
constexpr int XBYTES  = XROWS * 128;
constexpr int XBOX    = 88;
constexpr int XST     = 2;
constexpr int WST     = 4;
constexpr int WBYTES  = 8192;
constexpr int WO_BYTES = 131072;

constexpr int SM_WO   = 0;
constexpr int SM_X    = SM_WO + WO_BYTES;
constexpr int SM_W    = SM_X + XST * XBYTES;
constexpr int SM_BAR  = SM_W + WST * WBYTES;
constexpr int SM_TOTAL = SM_BAR + 256;
__host__ __device__ constexpr int sm_zin(int i) { return SM_X + (i >> 1) * XBYTES + (i & 1) * 16384; }
constexpr int SM_OSTG  = SM_W;
constexpr int SM_ZFIX  = SM_W + 16384;

constexpr int BAR_WFULL  = 0;
constexpr int BAR_WEMPTY = BAR_WFULL + WST;
constexpr int BAR_XFULL  = BAR_WEMPTY + WST;
constexpr int BAR_XEMPTY = BAR_XFULL + XST;
constexpr int BAR_WO     = BAR_XEMPTY + XST;
constexpr int BAR_PAR    = BAR_WO + 1;
constexpr int BAR_Z      = BAR_PAR + 1;
constexpr int BAR_RETRY  = BAR_Z + 4;

constexpr int SM_PAR   = SM_BAR + 240;
constexpr int NTHREADS = 256;
constexpr int MS = 2;
constexpr int AS = 2;
constexpr int HS = 4;
constexpr int HS3 = 4;
#define ZDELAY0 650
#define ZDELAY1 600
#define ZDELAY2 650
#define ZDELAY3 600

__device__ uint4 g_zx[2][8 * 4 * 4096];
__device__ unsigned int g_ticket;

#define PROF(i)
#define PROFG(i)

__device__ __forceinline__ uint32_t smem_u32(const void* p) { return (uint32_t)__cvta_generic_to_shared(p); }

__device__ __forceinline__ void mbar_init(uint32_t bar, uint32_t cnt) {
    asm volatile("mbarrier.init.shared::cta.b64 [%0], %1;" ::"r"(bar), "r"(cnt));
}
__device__ __forceinline__ void mbar_expect_tx(uint32_t bar, uint32_t bytes) {
    asm volatile("mbarrier.arrive.expect_tx.shared::cta.b64 _, [%0], %1;" ::"r"(bar), "r"(bytes) : "memory");
}
__device__ __forceinline__ void mbar_arrive(uint32_t bar) {
    asm volatile("mbarrier.arrive.shared::cta.b64 _, [%0];" ::"r"(bar) : "memory");
}
__device__ __forceinline__ void mbar_wait(uint32_t bar, uint32_t parity) {
    asm volatile(
        "{\n"
        ".reg .pred p;\n"
        "WAIT_LOOP:\n"
        "mbarrier.try_wait.parity.shared::cta.b64 p, [%0], %1;\n"
        "@p bra WAIT_DONE;\n"
        "bra WAIT_LOOP;\n"
        "WAIT_DONE:\n"
        "}\n" ::"r"(bar), "r"(parity) : "memory");
}
__device__ __forceinline__ void tma_load_3d(uint32_t dst, const CUtensorMap* m, uint32_t bar, int c0, int c1, int c2) {
    asm volatile("cp.async.bulk.tensor.3d.shared::cluster.global.mbarrier::complete_tx::bytes [%0], [%1, {%3, %4, %5}], [%2];"
                 ::"r"(dst), "l"(m), "r"(bar), "r"(c0), "r"(c1), "r"(c2) : "memory");
}
__device__ __forceinline__ void tma_load_2d(uint32_t dst, const CUtensorMap* m, uint32_t bar, int c0, int c1) {
    asm volatile("cp.async.bulk.tensor.2d.shared::cluster.global.mbarrier::complete_tx::bytes [%0], [%1, {%3, %4}], [%2];"
                 ::"r"(dst), "l"(m), "r"(bar), "r"(c0), "r"(c1) : "memory");
}
__device__ __forceinline__ void prefetch_tmap(const CUtensorMap* m) {
    asm volatile("prefetch.tensormap [%0];" ::"l"(m) : "memory");
}
__device__ __forceinline__ void wgmma_fence() { asm volatile("wgmma.fence.sync.aligned;" ::: "memory"); }
__device__ __forceinline__ void wgmma_commit() { asm volatile("wgmma.commit_group.sync.aligned;" ::: "memory"); }
template <int N> __device__ __forceinline__ void wgmma_wait() {
    asm volatile("wgmma.wait_group.sync.aligned %0;" ::"n"(N) : "memory");
}
template <int N> __device__ __forceinline__ void fence_regs(float (&d)[N]) {
#pragma unroll
    for (int i = 0; i < N; i++) asm volatile("" : "+f"(d[i]) :: "memory");
}
__device__ __forceinline__ void ldsm_x4_trans(uint32_t (&r)[4], uint32_t addr) {
    asm volatile("ldmatrix.sync.aligned.m8n8.x4.trans.shared.b16 {%0, %1, %2, %3}, [%4];"
                 : "=r"(r[0]), "=r"(r[1]), "=r"(r[2]), "=r"(r[3]) : "r"(addr) : "memory");
}
__device__ __forceinline__ void stsm_x4(uint32_t addr, uint32_t a, uint32_t b, uint32_t c, uint32_t d) {
    asm volatile("stmatrix.sync.aligned.m8n8.x4.shared.b16 [%0], {%1, %2, %3, %4};"
                 ::"r"(addr), "r"(a), "r"(b), "r"(c), "r"(d) : "memory");
}
__device__ __forceinline__ void st_relaxed_v4(void* p, uint32_t a, uint32_t b, uint32_t c, uint32_t d) {
    asm volatile("st.relaxed.gpu.global.v4.b32 [%0], {%1, %2, %3, %4};" ::"l"(p), "r"(a), "r"(b), "r"(c), "r"(d) : "memory");
}
__device__ __forceinline__ void bulk_load(uint32_t dst, const void* src, uint32_t bytes, uint32_t bar) {
    asm volatile("cp.async.bulk.shared::cluster.global.mbarrier::complete_tx::bytes [%0], [%1], %2, [%3];"
                 ::"r"(dst), "l"(src), "r"(bytes), "r"(bar) : "memory");
}
__device__ __forceinline__ uint32_t clock_now() {
    uint32_t t;
    asm volatile("mov.u32 %0, %%clock;" : "=r"(t) :: "memory");
    return t;
}
template <int BIT>
__device__ __forceinline__ void sched_fence(uint32_t zero) {
    asm volatile("{\n.reg .pred p;\n.reg .b32 t;\nand.b32 t, %0, %1;\nsetp.eq.u32 p, t, 0;\n@p bra SF_DONE;\ntrap;\nSF_DONE:\n}\n"
                 ::"r"(zero), "n"(1u << BIT) : "memory");
}
__device__ __forceinline__ float tanh_fast(float x) {
    float y;
    asm volatile("tanh.approx.f32 %0, %1;" : "=f"(y) : "f"(x));
    return y;
}
__device__ __forceinline__ void load_w_frags(uint32_t (&f)[4][4], uint32_t wa) {
#pragma unroll
    for (int kk = 0; kk < 4; kk++) ldsm_x4_trans(f[kk], wa + kk * 1024);
}
__device__ __forceinline__ void scale_w_frag(uint32_t (&f)[4]) {
    asm volatile("mul.rn.bf16x2 %0, %0, %1;" : "+r"(f[1]) : "r"(0x3F003F00u));
    asm volatile("mul.rn.bf16x2 %0, %0, %1;" : "+r"(f[3]) : "r"(0x3F003F00u));
}
__device__ __forceinline__ uint32_t pack_bf16(float lo, float hi) {
    uint32_t r;
    asm("cvt.rn.bf16x2.f32 %0, %1, %2;" : "=r"(r) : "f"(hi), "f"(lo));
    return r;
}
__device__ __forceinline__ uint64_t make_desc(uint32_t addr, uint32_t lbo_bytes, uint32_t sbo_bytes) {
    return (uint64_t)((addr & 0x3FFFF) >> 4) | ((uint64_t)(lbo_bytes >> 4) << 16) | ((uint64_t)(sbo_bytes >> 4) << 32) |
           ((uint64_t)1 << 62);
}

#define R8(d, o) "+f"(d[o + 0]), "+f"(d[o + 1]), "+f"(d[o + 2]), "+f"(d[o + 3]), "+f"(d[o + 4]), "+f"(d[o + 5]), "+f"(d[o + 6]), "+f"(d[o + 7])

__device__ __forceinline__ void wgmma_m64n128k16_rs(float (&d)[64], const uint32_t (&a)[4], uint64_t descB) {
    asm volatile(
        "wgmma.mma_async.sync.aligned.m64n128k16.f32.bf16.bf16 "
        "{%0, %1, %2, %3, %4, %5, %6, %7, %8, %9, %10, %11, %12, %13, %14, %15, "
        "%16, %17, %18, %19, %20, %21, %22, %23, %24, %25, %26, %27, %28, %29, %30, %31, "
        "%32, %33, %34, %35, %36, %37, %38, %39, %40, %41, %42, %43, %44, %45, %46, %47, "
        "%48, %49, %50, %51, %52, %53, %54, %55, %56, %57, %58, %59, %60, %61, %62, %63}, "
        "{%64, %65, %66, %67}, %68, 1, -1, 1, 1;\n"
        : R8(d, 0), R8(d, 8), R8(d, 16), R8(d, 24), R8(d, 32), R8(d, 40), R8(d, 48), R8(d, 56)
        : "r"(a[0]), "r"(a[1]), "r"(a[2]), "r"(a[3]), "l"(descB));
}

__device__ __forceinline__ void wgmma_m64n64k16_rs(float (&d)[32], const uint32_t (&a)[4], uint64_t descB, int scale_d) {
    asm volatile(
        "{\n"
        ".reg .pred p;\n"
        "setp.ne.b32 p, %37, 0;\n"
        "wgmma.mma_async.sync.aligned.m64n64k16.f32.bf16.bf16 "
        "{%0, %1, %2, %3, %4, %5, %6, %7, %8, %9, %10, %11, %12, %13, %14, %15, "
        "%16, %17, %18, %19, %20, %21, %22, %23, %24, %25, %26, %27, %28, %29, %30, %31}, "
        "{%32, %33, %34, %35}, %36, p, -1, 1, 1;\n"
        "}\n"
        : R8(d, 0), R8(d, 8), R8(d, 16), R8(d, 24)
        : "r"(a[0]), "r"(a[1]), "r"(a[2]), "r"(a[3]), "l"(descB), "r"(scale_d));
}

template <int OFF>
__device__ __forceinline__ void wgmma_m64n128k16_rs_half(float (&d)[128], const uint32_t (&a)[4], uint64_t descB) {
    asm volatile(
        "wgmma.mma_async.sync.aligned.m64n128k16.f32.bf16.bf16 "
        "{%0, %1, %2, %3, %4, %5, %6, %7, %8, %9, %10, %11, %12, %13, %14, %15, "
        "%16, %17, %18, %19, %20, %21, %22, %23, %24, %25, %26, %27, %28, %29, %30, %31, "
        "%32, %33, %34, %35, %36, %37, %38, %39, %40, %41, %42, %43, %44, %45, %46, %47, "
        "%48, %49, %50, %51, %52, %53, %54, %55, %56, %57, %58, %59, %60, %61, %62, %63}, "
        "{%64, %65, %66, %67}, %68, 1, 1, 1, 0;\n"
        : R8(d, OFF + 0), R8(d, OFF + 8), R8(d, OFF + 16), R8(d, OFF + 24), R8(d, OFF + 32), R8(d, OFF + 40), R8(d, OFF + 48), R8(d, OFF + 56)
        : "r"(a[0]), "r"(a[1]), "r"(a[2]), "r"(a[3]), "l"(descB));
}
template <int OFF> __device__ __forceinline__ void fence_half(float (&d)[128]) {
#pragma unroll
    for (int i = 0; i < 64; i++) asm volatile("" : "+f"(d[OFF + i]) :: "memory");
}

template <int Q0, int N> struct GateGroup { static constexpr int J = 2 * (Q0 ^ (N >> 1)) + (N & 1); };

template <int Q0, int N>
__device__ __forceinline__ void gate_mufu(float (&acc)[128]) {
    constexpr int J = GateGroup<Q0, N>::J;
#pragma unroll
    for (int i = 0; i < 16; i++) acc[16 * J + i] = tanh_fast(acc[16 * J + i]);
}
template <int Q0, int N>
__device__ __forceinline__ void gate_finish(float (&acc)[128], uint8_t* zdst) {
    constexpr int J = GateGroup<Q0, N>::J;
    uint32_t zp[4];
#pragma unroll
    for (int i = 0; i < 4; i++) {
        const int r = 16 * J + 4 * i;
        zp[i] = __vmaxu2(pack_bf16(acc[r] * fmaf(acc[r + 2], -0.5f, -0.5f), acc[r + 1] * fmaf(acc[r + 3], -0.5f, -0.5f)), 0x00010001u);
    }
    st_relaxed_v4(zdst + (J >> 1) * 65536 + (J & 1) * 8192, zp[0], zp[1], zp[2], zp[3]);
    if (N & 1) asm volatile("bar.arrive %0, 160;" ::"n"(2 + (N >> 1)) : "memory");
}

template <int Q0>
__device__ __forceinline__ void tail_gemm1(float (&acc)[128], uint32_t (&afr)[2][4][4], uint32_t sb, int ws, int wph, uint32_t a_lane_off,
                                           uint8_t* zdst, int lane, uint32_t zero) {
    constexpr int OA = (Q0 >> 1) * 64;
    constexpr int OB = 64 - OA;
    const uint32_t bars = sb + SM_BAR;
    uint32_t fa[4][4], fb[4][4], fc[4][4];
    const int ws0 = ws;
    auto wtile = [&](int tap) { return sb + SM_W + ((ws0 + tap) & (WST - 1)) * WBYTES + a_lane_off; };
    auto wwait = [&](int tap) {
        const int st = ws0 + tap;
        mbar_wait(bars + 8 * (BAR_WFULL + (st & (WST - 1))), wph ^ ((st >> 2) & 1));
    };
    auto load = [&](uint32_t (&f)[4][4], int tap) { load_w_frags(f, wtile(tap)); };
    auto issueA = [&](uint32_t (&f)[4][4], int tap) {
        const uint64_t db = make_desc(sb + SM_X + XBYTES + (8 - 2 * tap) * 128 + OA * 256, 16, 1024);
#pragma unroll
        for (int h = 0; h < AS; h++) {
#pragma unroll
            for (int kk = h * (4 / AS); kk < (h + 1) * (4 / AS); kk++) scale_w_frag(f[kk]);
            wgmma_fence();
#pragma unroll
            for (int kk = h * (4 / AS); kk < (h + 1) * (4 / AS); kk++) wgmma_m64n128k16_rs_half<OA>(acc, f[kk], db + kk * 2);
            wgmma_commit();
        }
    };
    auto issueB = [&](uint32_t (&f)[4][4], int tap) {
        const uint64_t db = make_desc(sb + SM_X + XBYTES + (8 - 2 * tap) * 128 + OB * 256, 16, 1024);
        wgmma_fence();
#pragma unroll
        for (int kk = 0; kk < 4; kk++) wgmma_m64n128k16_rs_half<OB>(acc, f[kk], db + kk * 2);
        wgmma_commit();
    };
    mbar_wait(bars + 8 * (BAR_XFULL + 1), 1);
    wwait(0); load(fa, 0);
    __syncwarp();
    if (lane == 0) mbar_arrive(bars + 8 * (BAR_WEMPTY + ws0));
    wwait(1); load(fb, 1);
    wwait(2); load(fc, 2);
    issueA(fa, 0); wgmma_wait<AS>();
    wwait(3); load(afr[0], 3);
    issueA(fb, 1);
    issueA(fc, 2);
    wwait(4); load(afr[1], 4);
    issueA(afr[0], 3);
    issueA(afr[1], 4);
    if (threadIdx.x == 0) PROF(24);
    issueB(fa, 0);
    issueB(fb, 1);
    wgmma_wait<2>();
    fence_half<OA>(acc);
    sched_fence<0>(zero);
    gate_mufu<Q0, 0>(acc); gate_mufu<Q0, 1>(acc);
    gate_finish<Q0, 0>(acc, zdst); gate_finish<Q0, 1>(acc, zdst);
    sched_fence<1>(zero);
    issueB(fc, 2);
    issueB(afr[0], 3);
    sched_fence<2>(zero);
    gate_mufu<Q0, 2>(acc); gate_mufu<Q0, 3>(acc);
    sched_fence<3>(zero);
    issueB(afr[1], 4);
    sched_fence<4>(zero);
    gate_finish<Q0, 2>(acc, zdst); gate_finish<Q0, 3>(acc, zdst);
    wgmma_wait<0>();
    fence_half<OB>(acc);
    if (threadIdx.x == 0) PROF(3);
    gate_mufu<Q0, 4>(acc);
    gate_mufu<Q0, 5>(acc);
    gate_finish<Q0, 4>(acc, zdst);
    gate_finish<Q0, 5>(acc, zdst);
    sched_fence<5>(zero);
    gate_mufu<Q0, 6>(acc);
    gate_mufu<Q0, 7>(acc);
    gate_finish<Q0, 6>(acc, zdst);
    gate_finish<Q0, 7>(acc, zdst);
}

__device__ __forceinline__ void fetch_slot(int i, uint32_t sb, const uint8_t* zsrc, int q, int lane) {
    const uint32_t bars = sb + SM_BAR;
    asm volatile("bar.sync %0, 160;" ::"r"(2 + i) : "memory");
    if (lane == 0) {
        uint32_t t;
        asm volatile("mov.u32 %0, %%clock;" : "=r"(t) : "r"(lane) : "memory");
        const uint32_t delay = (i == 0) ? ZDELAY0 : (i == 1) ? ZDELAY1 : (i == 2) ? ZDELAY2 : ZDELAY3;
        while (clock_now() - t < delay) {}
        mbar_expect_tx(bars + 8 * (BAR_Z + i), 16384);
        bulk_load(sb + sm_zin(i), zsrc + (q ^ i) * 16384, 16384, bars + 8 * (BAR_Z + i));
        PROF(26 + i);
    }
    __syncwarp();
}

template <int I>
__device__ __forceinline__ void z_load(uint32_t (&z)[8][4], uint32_t sb, int warp, int lane) {
    mbar_wait(sb + SM_BAR + 8 * (BAR_Z + I), 0);
#pragma unroll
    for (int j = 0; j < 8; j++) ldsm_x4_trans(z[j], sb + sm_zin(I) + warp * 4096 + j * 512 + lane * 16);
}
__device__ __forceinline__ bool z_check(const uint32_t (&z)[8][4]) {
    uint32_t m0 = 0xFFFFFFFFu, m1 = 0xFFFFFFFFu;
#pragma unroll
    for (int j = 0; j < 8; j++) {
        m0 = __vimin3_u16x2(m0, z[j][0], z[j][1]);
        m1 = __vimin3_u16x2(m1, z[j][2], z[j][3]);
    }
    m0 = __vminu2(m0, m1);
    return __all_sync(0xffffffffu, ((m0 & 0xFFFFu) != 0u) && ((m0 >> 16) != 0u));
}
__device__ __forceinline__ void z_issue(float (&acc2)[64], uint32_t (&z)[8][4], uint32_t sb, int beta) {
    const uint64_t db = make_desc(sb + SM_WO + beta * 16384, 65536, 1024);
#pragma unroll
    for (int h = 0; h < HS; h++) {
#pragma unroll
        for (int j = h * (8 / HS); j < (h + 1) * (8 / HS); j++)
            asm volatile("" : "+r"(z[j][0]), "+r"(z[j][1]), "+r"(z[j][2]), "+r"(z[j][3]) :: "memory");
        wgmma_fence();
#pragma unroll
        for (int j = h * (8 / HS); j < (h + 1) * (8 / HS); j++) wgmma_m64n128k16_rs(acc2, z[j], db + j * 128);
        wgmma_commit();
    }
}
__device__ __forceinline__ bool wg_any(bool p) {
    uint32_t r;
    asm volatile("{\n.reg .pred a, b;\nsetp.ne.u32 a, %1, 0;\nbarrier.cta.red.or.aligned.pred b, 1, 128, a;\nselp.u32 %0, 1, 0, b;\n}\n"
                 : "=r"(r) : "r"((uint32_t)p) : "memory");
    return r != 0;
}
template <int I>
__device__ __forceinline__ void z_repair(float (&acc2)[64], uint32_t sb, const uint8_t* src, int beta, int warp, int lane, uint32_t mine,
                                         uint32_t& rph) {
    if (!wg_any(mine != 0u)) return;
    uint32_t z[8][4];
    if (mine) {
        const uint32_t zo = sb + sm_zin(I) + warp * 4096;
        const uint32_t zs = sb + SM_ZFIX + warp * 4096;
        const uint32_t bar = sb + SM_BAR + 8 * (BAR_RETRY + warp);
        int spins = 0;
        do {
            __syncwarp();
            if (lane == 0) {
                mbar_expect_tx(bar, 4096);
                bulk_load(zs, src, 4096, bar);
            }
            mbar_wait(bar, rph);
            rph ^= 1;
#pragma unroll
            for (int j = 0; j < 8; j++) ldsm_x4_trans(z[j], zs + j * 512 + lane * 16);
        } while (!z_check(z) && ++spins < (1 << 16));
#pragma unroll
        for (int j = 0; j < 8; j++) {
            uint32_t o[4];
            ldsm_x4_trans(o, zo + j * 512 + lane * 16);
#pragma unroll
            for (int k = 0; k < 4; k++) z[j][k] &= __vcmpeq2(o[k], 0u);
        }
    } else {
#pragma unroll
        for (int j = 0; j < 8; j++)
#pragma unroll
            for (int k = 0; k < 4; k++) z[j][k] = 0u;
    }
    z_issue(acc2, z, sb, beta);
    wgmma_wait<0>();
}

template <int H>
__device__ __forceinline__ void store_half(const float (&a)[64], const float (&b)[32], uint32_t stg, const __nv_bfloat16* orow, int tok0, int lane) {
    const uint32_t st = stg + H * 2048 + (lane & 15) * 128;
    const int csel = lane >> 4, sw = lane & 7;
#pragma unroll
    for (int j2 = 0; j2 < 4; j2++) {
        const int j = 2 * j2, o = 32 * H + 4 * j;
        const uint32_t r0 = pack_bf16(a[o + 0] + b[4 * j + 0], a[o + 1] + b[4 * j + 1]);
        const uint32_t r1 = pack_bf16(a[o + 2] + b[4 * j + 2], a[o + 3] + b[4 * j + 3]);
        const uint32_t r2 = pack_bf16(a[o + 4] + b[4 * j + 4], a[o + 5] + b[4 * j + 5]);
        const uint32_t r3 = pack_bf16(a[o + 6] + b[4 * j + 6], a[o + 7] + b[4 * j + 7]);
        stsm_x4(st + (((j + csel) ^ sw) << 4), r0, r1, r2, r3);
    }
    __syncwarp();
#pragma unroll
    for (int i = 0; i < 4; i++) {
        const int r = 4 * i + (lane >> 3);
        uint32_t v0, v1, v2, v3;
        asm volatile("ld.shared.v4.b32 {%0, %1, %2, %3}, [%4];" : "=r"(v0), "=r"(v1), "=r"(v2), "=r"(v3)
                     : "r"(stg + H * 2048 + r * 128 + (((lane & 7) ^ (r & 7)) << 4)) : "memory");
        const int dt = (i & 1) * 16 + (i >> 1) * 2;
        asm volatile("{\n.reg .pred p;\nsetp.lt.s32 p, %5, %6;\n@p st.global.v4.b32 [%0], {%1, %2, %3, %4};\n}\n"
                     ::"l"(orow + dt * D_CH + H * 64), "r"(v0), "r"(v1), "r"(v2), "r"(v3), "r"(tok0), "r"(T_LEN - dt) : "memory");
    }
}

__global__ void __launch_bounds__(NTHREADS, 1)
wavenet_fused_kernel(const __grid_constant__ CUtensorMap mapX, const __grid_constant__ CUtensorMap mapW,
                     const __grid_constant__ CUtensorMap mapWo, __nv_bfloat16* __restrict__ out, const uint32_t zero) {
    extern __shared__ __align__(1024) uint8_t smem_raw[];
    const uint32_t sb = smem_u32(smem_raw);
    const uint32_t bars = sb + SM_BAR;
    const int warp = threadIdx.x >> 5;
    const int lane = threadIdx.x & 31;
    const int cg = blockIdx.x & 15;
    const int tt = blockIdx.x >> 4;
    const int batch = tt >> 2;
    const int t0 = (tt & 3) * NTOK;
    const int c4 = cg & 3, q = cg >> 2;

    if (threadIdx.x == 128) {
        PROFG(0);
        const uint32_t xf = bars + 8 * BAR_XFULL;
        mbar_init(bars + 8 * BAR_WFULL, 1);
        mbar_expect_tx(bars + 8 * BAR_WFULL, WBYTES);
        tma_load_3d(sb + SM_W, &mapW, bars + 8 * BAR_WFULL, cg * 32, 0, 0);
        mbar_init(xf, 1);
        mbar_expect_tx(xf, XBYTES);
#pragma unroll
        for (int j = 0; j < 3; j++) tma_load_3d(sb + SM_X + j * XBOX * 128, &mapX, xf, 0, t0 - 8 + j * XBOX, batch);
#pragma unroll
        for (int i = 1; i < WST; i++) {
            mbar_init(bars + 8 * (BAR_WFULL + i), 1);
            mbar_expect_tx(bars + 8 * (BAR_WFULL + i), WBYTES);
            tma_load_3d(sb + SM_W + i * WBYTES, &mapW, bars + 8 * (BAR_WFULL + i), cg * 32, i * 512, 0);
        }
        asm volatile("fence.mbarrier_init.release.cluster;" ::: "memory");
    }
    if (threadIdx.x == 160) prefetch_tmap(&mapX);
    if (threadIdx.x == 192) {
        for (int i = 0; i < WST; i++) mbar_init(bars + 8 * (BAR_WEMPTY + i), 4);
        mbar_init(bars + 8 * (BAR_XFULL + 1), 1);
        for (int i = 0; i < XST; i++) mbar_init(bars + 8 * (BAR_XEMPTY + i), 4);
        mbar_init(bars + 8 * BAR_WO, 1);
        mbar_init(bars + 8 * BAR_PAR, 1);
        for (int i = 0; i < 4; i++) {
            mbar_init(bars + 8 * (BAR_Z + i), 1);
            mbar_init(bars + 8 * (BAR_RETRY + i), 1);
        }
        asm volatile("fence.mbarrier_init.release.cluster;" ::: "memory");
    }

    if (warp >= 4) {
        asm volatile("bar.sync 7, 128;" ::: "memory");
        asm volatile("bar.arrive 0, 256;" ::: "memory");
        if (warp == 4) {
            if (lane == 0) {
                int ws = 0, wph = 0;
                for (int kc = 0; kc < 8; kc++) {
                    const int xs = kc & 1;
                    if (kc > 0) {
                        mbar_wait(bars + 8 * (BAR_XEMPTY + xs), ((kc >> 1) & 1) ^ 1);
                        const uint32_t xf = bars + 8 * (BAR_XFULL + xs);
                        mbar_expect_tx(xf, XBYTES);
                        const uint32_t xd = sb + SM_X + xs * XBYTES;
#pragma unroll
                        for (int j = 0; j < 3; j++) tma_load_3d(xd + j * XBOX * 128, &mapX, xf, kc * 64, t0 - 8 + j * XBOX, batch);
                    } else {
                        prefetch_tmap(&mapWo);
                    }
                    for (int tap = (kc == 0 ? WST : 0); tap < 5; tap++) {
                        mbar_wait(bars + 8 * (BAR_WEMPTY + ws), wph);
                        const uint32_t wf = bars + 8 * (BAR_WFULL + ws);
                        mbar_expect_tx(wf, WBYTES);
                        tma_load_3d(sb + SM_W + ws * WBYTES, &mapW, wf, cg * 32, tap * 512 + kc * 64, 0);
                        if (++ws == WST) { ws = 0; wph ^= 1; }
                        const int it = kc * 5 + tap - 10;
                        if (it >= 0 && it < 16) {
                            const uint32_t wob = bars + 8 * BAR_WO;
                            if (it == 0) mbar_expect_tx(wob, WO_BYTES);
                            tma_load_2d(sb + SM_WO + (it & 1) * 65536 + (it >> 1) * 8192, &mapWo, wob, c4 * 128 + (it & 1) * 64, (it >> 1) * 64);
                        }
                    }
                }
            }
            __syncwarp();
        } else if (warp == 5) {
            unsigned int par = 0;
            if (lane == 0) par = (atomicAdd(&g_ticket, 1u) >> 7) & 1u;
            par = __shfl_sync(0xffffffffu, par, 0);
            __nanosleep(1500);
            uint4* mine = &g_zx[par][tt * 4 * 4096 + q * 1024 + 2 * c4 * 32];
#pragma unroll 1
            for (int i = 0; i < 32; i++) {
                mine[(i >> 3) * 4096 + ((i >> 1) & 3) * 256 + (i & 1) * 32 + lane] = make_uint4(0u, 0u, 0u, 0u);
                __nanosleep(100);
            }
            __syncwarp();
            if (lane == 0) {
                asm volatile("st.shared.u32 [%0], %1;" ::"r"(sb + SM_PAR), "r"(par) : "memory");
                mbar_arrive(bars + 8 * BAR_PAR);
            }
            uint4* clr = &g_zx[par ^ 1][blockIdx.x * 1024];
#pragma unroll 1
            for (int i = 0; i < 32; i++) {
                clr[i * 32 + lane] = make_uint4(0u, 0u, 0u, 0u);
                __nanosleep(64);
            }
        }
        mbar_wait(bars + 8 * BAR_PAR, 0);
        uint32_t par;
        asm volatile("ld.shared.u32 %0, [%1];" : "=r"(par) : "r"(sb + SM_PAR) : "memory");
        const uint8_t* zsrc = reinterpret_cast<const uint8_t*>(&g_zx[par][(tt * 4 + q) * 4096]);
        fetch_slot(7 - warp, sb, zsrc, q, lane);
    } else {
        float acc[128];
#pragma unroll
        for (int i = 0; i < 128; i++) acc[i] = 0.f;
        uint32_t afr[2][4][4];
        const int lk = ((lane >> 4) << 3) + (lane & 7);
        const uint32_t a_lane_off = ((lane >> 3) & 1) * 4096 + lk * 64 + ((warp ^ ((lk >> 1) & 3)) << 4);
        int ws = 0, wph = 0;
        uint32_t par = 0;
        asm volatile("bar.sync 0, 256;" ::: "memory");
        if (threadIdx.x == 0) PROF(1);
        {
#pragma unroll
            for (int k = 0; k < 4; k++) afr[0][0][k] = 0x3c003c00u + lane * 0x00010001u;
            const uint64_t dbw = make_desc(sb + SM_WO, 16, 1024);
            const uint32_t tw = clock_now();
            while (clock_now() - tw < 200u) {}
#pragma unroll 1
            for (int it = 0; it < 3; it++) {
                wgmma_fence();
                wgmma_m64n128k16_rs_half<0>(acc, afr[0][0], dbw);
                wgmma_m64n128k16_rs_half<64>(acc, afr[0][0], dbw + 1024);
                wgmma_m64n128k16_rs_half<0>(acc, afr[0][0], dbw + 2);
                wgmma_m64n128k16_rs_half<64>(acc, afr[0][0], dbw + 1026);
                wgmma_commit();
                wgmma_wait<0>();
            }
            fence_regs(acc);
#pragma unroll
            for (int i = 0; i < 128; i++) acc[i] = 0.f;
            fence_regs(acc);
        }
#pragma unroll 1
        for (int kc2 = 0; kc2 < 4; kc2++) {
#pragma unroll
            for (int u = 0; u < 10; u++) {
                const int xs = u / 5;
                const int tap = u % 5;
                if (u == 5 && kc2 == 3) break;
                if (tap == 0) mbar_wait(bars + 8 * (BAR_XFULL + xs), kc2 & 1);
                mbar_wait(bars + 8 * (BAR_WFULL + ws), wph);
                if (kc2 == 0 && u == 0 && threadIdx.x == 0) PROF(2);
                const uint32_t wa = sb + SM_W + ws * WBYTES + a_lane_off;
                load_w_frags(afr[u & 1], wa);
                __syncwarp();
                if (lane == 0) mbar_arrive(bars + 8 * (BAR_WEMPTY + ws));
                if (++ws == WST) { ws = 0; wph ^= 1; }
                const uint64_t db = make_desc(sb + SM_X + xs * XBYTES + (8 - 2 * tap) * 128, 16, 1024);
#pragma unroll
                for (int h = 0; h < MS; h++) {
#pragma unroll
                    for (int kk = h * (4 / MS); kk < (h + 1) * (4 / MS); kk++) scale_w_frag(afr[u & 1][kk]);
                    wgmma_fence();
#pragma unroll
                    for (int kk = h * (4 / MS); kk < (h + 1) * (4 / MS); kk++) {
                        wgmma_m64n128k16_rs_half<0>(acc, afr[u & 1][kk], db + kk * 2);
                        wgmma_m64n128k16_rs_half<64>(acc, afr[u & 1][kk], db + kk * 2 + 1024);
                    }
                    wgmma_commit();
                }
                if (u == 2 && kc2 == 3) {
                    mbar_wait(bars + 8 * BAR_PAR, 0);
                    asm volatile("ld.shared.u32 %0, [%1];" : "=r"(par) : "r"(sb + SM_PAR) : "memory");
                    mbar_wait(bars + 8 * BAR_WO, 0);
                }
                wgmma_wait<MS>();
                if (tap == 0 && (u > 0 || kc2 > 0)) {
                    if (lane == 0) mbar_arrive(bars + 8 * (BAR_XEMPTY + (xs ^ 1)));
                }
            }
        }
        uint8_t* zx = reinterpret_cast<uint8_t*>(&g_zx[par][tt * 4 * 4096]);
        uint8_t* zdst = zx + q * 16384 + (2 * c4 + (warp >> 1)) * 512 + (warp & 1) * 256 +
                        ((lane >> 1) & 1) * 4096 + (lane & 1) * 128 + (lane >> 2) * 16;
        switch (q) {
            case 0: tail_gemm1<0>(acc, afr, sb, ws, wph, a_lane_off, zdst, lane, zero); break;
            case 1: tail_gemm1<1>(acc, afr, sb, ws, wph, a_lane_off, zdst, lane, zero); break;
            case 2: tail_gemm1<2>(acc, afr, sb, ws, wph, a_lane_off, zdst, lane, zero); break;
            default: tail_gemm1<3>(acc, afr, sb, ws, wph, a_lane_off, zdst, lane, zero); break;
        }
        if (threadIdx.x == 0) PROF(4);

        float acc2[64], acc3a[32], acc3b[32];
#pragma unroll
        for (int i = 0; i < 64; i++) acc2[i] = 0.f;
        const uint32_t stg = sb + SM_OSTG + warp * 4096;
        const int tok0 = t0 + q * 64 + (warp >> 1) * 32 + (warp & 1) * 4 + (lane >> 4) * 8 + ((lane >> 3) & 1);
        const __nv_bfloat16* orow = out + ((size_t)batch * T_LEN + tok0) * D_CH + c4 * 128 + (lane & 7) * 8;
        uint32_t bad;
        {
            uint32_t za[3][8][4];
            z_load<0>(za[0], sb, warp, lane);
            if (threadIdx.x == 0) PROF(12);
            z_issue(acc2, za[0], sb, q ^ 0);
            z_load<1>(za[1], sb, warp, lane);
            bad = z_check(za[0]) ? 0u : 1u;
            if (threadIdx.x == 0) PROF(13);
            z_issue(acc2, za[1], sb, q ^ 1);
            z_load<2>(za[2], sb, warp, lane);
            bad |= z_check(za[1]) ? 0u : 2u;
            if (threadIdx.x == 0) PROF(14);
            z_issue(acc2, za[2], sb, q ^ 2);
            wgmma_wait<2 * HS>();
            z_load<3>(za[0], sb, warp, lane);
            bad |= z_check(za[2]) ? 0u : 4u;
            if (threadIdx.x == 0) PROF(15);
            const uint64_t db = make_desc(sb + SM_WO + (q ^ 3) * 16384, 65536, 1024);
#pragma unroll
            for (int h = 0; h < HS3; h++) {
#pragma unroll
                for (int j = h * (8 / HS3); j < (h + 1) * (8 / HS3); j++)
                    asm volatile("" : "+r"(za[0][j][0]), "+r"(za[0][j][1]), "+r"(za[0][j][2]), "+r"(za[0][j][3]) :: "memory");
                wgmma_fence();
#pragma unroll
                for (int j = h * (8 / HS3); j < (h + 1) * (8 / HS3); j++) wgmma_m64n64k16_rs(acc3a, za[0][j], db + j * 128, j);
                wgmma_commit();
            }
#pragma unroll
            for (int j = 0; j < 8; j++) wgmma_m64n64k16_rs(acc3b, za[0][j], db + j * 128 + 4096, j);
            wgmma_commit();
            wgmma_wait<1>();
            fence_regs(acc2);
            fence_regs(acc3a);
            if (threadIdx.x == 0) PROF(10);
            store_half<0>(acc2, acc3a, stg, orow, tok0, lane);
            sched_fence<7>(zero);
            bad |= z_check(za[0]) ? 0u : 8u;
        }
        wgmma_wait<0>();
        fence_regs(acc3b);
        store_half<1>(acc2, acc3b, stg, orow, tok0, lane);
        if (__builtin_expect(wg_any(bad != 0u), 0)) {
            const uint8_t* zsrc = zx + q * 65536 + warp * 4096;
            uint32_t rph = 0;
            z_repair<0>(acc2, sb, zsrc + (q ^ 0) * 16384, q ^ 0, warp, lane, bad & 1u, rph);
            z_repair<1>(acc2, sb, zsrc + (q ^ 1) * 16384, q ^ 1, warp, lane, bad & 2u, rph);
            z_repair<2>(acc2, sb, zsrc + (q ^ 2) * 16384, q ^ 2, warp, lane, bad & 4u, rph);
            z_repair<3>(acc2, sb, zsrc + (q ^ 3) * 16384, q ^ 3, warp, lane, bad & 8u, rph);
            fence_regs(acc2);
            __syncwarp();
            store_half<0>(acc2, acc3a, stg, orow, tok0, lane);
            store_half<1>(acc2, acc3b, stg, orow, tok0, lane);
        }
        if (threadIdx.x == 0) PROFG(11);
    }
}

typedef CUresult (*EncodeFn)(CUtensorMap*, CUtensorMapDataType, cuuint32_t, void*, const cuuint64_t*, const cuuint64_t*,
                             const cuuint32_t*, const cuuint32_t*, CUtensorMapInterleave, CUtensorMapSwizzle,
                             CUtensorMapL2promotion, CUtensorMapFloatOOBfill);

void encode(EncodeFn fn, CUtensorMap* m, const void* ptr, int rank, const cuuint64_t* dims, const cuuint64_t* strides,
            const cuuint32_t* box, CUtensorMapSwizzle sw) {
    cuuint32_t es[3] = {1, 1, 1};
    fn(m, CU_TENSOR_MAP_DATA_TYPE_BFLOAT16, rank, const_cast<void*>(ptr), dims, strides, box, es,
       CU_TENSOR_MAP_INTERLEAVE_NONE, sw, CU_TENSOR_MAP_L2_PROMOTION_L2_128B, CU_TENSOR_MAP_FLOAT_OOB_FILL_NONE);
}

}

extern "C" void kernel_launch(void* const* d_in, const int* in_sizes, int n_in, void* d_out, int out_size) {
    (void)in_sizes; (void)n_in; (void)out_size;
    static EncodeFn enc = nullptr;
    if (!enc) {
        void* fn = nullptr;
        cudaDriverEntryPointQueryResult qr;
        cudaGetDriverEntryPoint("cuTensorMapEncodeTiled", &fn, cudaEnableDefault, &qr);
        enc = (EncodeFn)fn;
        cudaFuncSetAttribute(wavenet_fused_kernel, cudaFuncAttributeMaxDynamicSharedMemorySize, SM_TOTAL);
    }
    CUtensorMap mX, mW, mWo;
    {
        cuuint64_t dims[3] = {512, (cuuint64_t)T_LEN, 2}, str[2] = {1024, (cuuint64_t)T_LEN * 1024};
        cuuint32_t box[3] = {64, XBOX, 1};
        encode(enc, &mX, d_in[0], 3, dims, str, box, CU_TENSOR_MAP_SWIZZLE_128B);
    }
    {
        cuuint64_t dims[3] = {512, 2560, 2}, str[2] = {2048, 1024};
        cuuint32_t box[3] = {32, 64, 2};
        encode(enc, &mW, d_in[1], 3, dims, str, box, CU_TENSOR_MAP_SWIZZLE_64B);
    }
    {
        cuuint64_t dims[2] = {512, 512}, str[1] = {1024};
        cuuint32_t box[2] = {64, 64};
        encode(enc, &mWo, d_in[2], 2, dims, str, box, CU_TENSOR_MAP_SWIZZLE_128B);
    }
    wavenet_fused_kernel<<<128, NTHREADS, SM_TOTAL>>>(mX, mW, mWo, (__nv_bfloat16*)d_out, 0u);
}
```
